```python
import torch

def _softmax(x, axis=-1):
    return torch.softmax(x, dim=axis)

def _gelu(x):
    return torch.nn.functional.gelu(x, approximate='tanh')

def _silu(x):
    return torch.nn.functional.silu(x)

def _sigmoid(x):
    return torch.sigmoid(x)

def _layernorm(x, axis=-1, eps=1e-05):
    m = x.mean(dim=axis, keepdim=True)
    v = x.var(dim=axis, keepdim=True, unbiased=False)
    return (x - m) / torch.sqrt(v + eps)

def _scatter_add(tgt, idx, src, axis=0):
    return tgt.clone().index_add_(axis, idx, src)

def _segment_sum(src, seg, n):
    out = torch.zeros((n,) + src.shape[1:], dtype=src.dtype)
    return out.index_add_(0, seg, src)

def _pad(x, pw):
    flat = tuple((v for pair in reversed(pw) for v in pair))
    return torch.nn.functional.pad(x, flat)
kernel_name = 'concat_heads__memory_aug_recurrent_mem_tr__ssm_conv_h3__prompt'

def setup_inputs():

    _w = lambda a: (lambda t: t.to(torch.bfloat16) if t.is_floating_point() else t)(torch.as_tensor(a))

    def _A_setup():
        B, S, Dm = (1, 2048, 640)
        H, Dh = (32, 128)
        M, seg = (8, 32)
        seg = min(seg, S)
        S = S // seg * seg
        return {'x': _w((lambda *s: torch.randn(*s, dtype=torch.bfloat16) * 0.05)(B, S, Dm)), 'mem0': _w((lambda *s: torch.randn(*s, dtype=torch.bfloat16) * 0.4)(B, M, Dm)), 'Wq': _w((lambda *s: torch.randn(*s, dtype=torch.bfloat16) * 6.4)(Dm, H, Dh) * Dm ** (-0.5)), 'Wk': _w((lambda *s: torch.randn(*s, dtype=torch.bfloat16) * 6.4)(Dm, H, Dh) * Dm ** (-0.5)), 'Wv': _w((lambda *s: torch.randn(*s, dtype=torch.bfloat16) * 0.4)(Dm, H, Dh) * Dm ** (-0.5)), 'Wo': _w((lambda *s: torch.randn(*s, dtype=torch.bfloat16) * 0.4)(H, Dh, Dm) * (H * Dh) ** (-0.5)), 'seg_len': seg}
    _A_in = _A_setup()

    def _B_setup():
        B, S, D = (1, 2048, 640)
        ks = 4
        return {'q': _w((lambda *s: torch.randn(*s, dtype=torch.bfloat16) * 0.05)(B, S, D)), 'k': _w((lambda *s: torch.randn(*s, dtype=torch.bfloat16) * 0.4)(B, S, D)), 'v': _w((lambda *s: torch.randn(*s, dtype=torch.bfloat16) * 0.4)(B, S, D)), 'shift_k': _w((lambda *s: torch.randn(*s, dtype=torch.bfloat16) * 0.4)(D, ks) * 0.5), 'ssm_k': _w((lambda *s: torch.randn(*s, dtype=torch.bfloat16) * 0.4)(D, S) * (1.0 / S ** 0.5)), 'ssm_D': _w((lambda *s: torch.randn(*s, dtype=torch.bfloat16) * 0.4)(D))}
    _B_in = _B_setup()
    return {'A_x': _A_in['x'], 'A_mem0': _A_in['mem0'], 'A_Wq': _A_in['Wq'], 'A_Wk': _A_in['Wk'], 'A_Wv': _A_in['Wv'], 'A_Wo': _A_in['Wo'], 'A_seg_len': _A_in['seg_len'], 'B_q': _B_in['q'], 'B_k': _B_in['k'], 'B_v': _B_in['v'], 'B_shift_k': _B_in['shift_k'], 'B_ssm_k': _B_in['ssm_k'], 'B_ssm_D': _B_in['ssm_D']}

def reference(A_x, A_mem0, A_Wq, A_Wk, A_Wv, A_Wo, A_seg_len, B_q, B_k, B_v, B_shift_k, B_ssm_k, B_ssm_D):

    def _A_ref(x, mem0, Wq, Wk, Wv, Wo, seg_len):
        B, S, Dm = x.shape
        H, Dh = (Wq.shape[1], Wq.shape[2])
        M = mem0.shape[1]
        scale = Dh ** (-0.5)
        n_seg = S // seg_len
        L = M + seg_len
        idx = torch.arange(L)
        mask = (idx[:, None] < M) | (idx[:, None] >= idx[None, :])
        mem = mem0
        outs = []
        for s in range(n_seg):
            xs = x[:, s * seg_len:(s + 1) * seg_len, :].clone()
            h = torch.concatenate([mem, xs], axis=1)
            q = torch.einsum('btd,dhe->bhte', h, Wq)
            k = torch.einsum('btd,dhe->bhte', h, Wk)
            v = torch.einsum('btd,dhe->bhte', h, Wv)
            scores = torch.einsum('bhqe,bhke->bhqk', q, k) * scale
            scores = torch.where(mask[None, None], scores, -1000000000.0)
            p = _softmax(scores, axis=-1)
            o = torch.einsum('bhqk,bhke->bhqe', p, v)
            o = torch.einsum('bhte,hed->btd', o, Wo)
            mem = o[:, :M, :].clone()
            outs.append(o[:, M:, :])
        return torch.concatenate(outs, axis=1)

    def _B_ref(q, k, v, shift_k, ssm_k, ssm_D):
        B, S, D = q.shape
        ks = shift_k.shape[-1]
        k_pad = _pad(k, ((0, 0), (ks - 1, 0), (0, 0)))
        k_shift = torch.zeros_like(k)
        for t in range(ks):
            k_shift = k_shift + k_pad[:, t:t + S, :] * shift_k[:, ks - 1 - t][None, None, :]
        kv = k_shift * v
        L = 2 * S
        kv_pad = _pad(kv, ((0, 0), (0, S), (0, 0)))
        kf_pad = _pad(ssm_k, ((0, 0), (0, S)))
        kv_f = (lambda x, axes=(-2, -1): torch.fft.rfft2(x.float(), dim=axes))(kv_pad[:, None, :, :], axes=(1, 2))
        kf_f = (lambda x, axes=(-2, -1): torch.fft.rfft2(x.float(), dim=axes))(kf_pad[:, None, :], axes=(1, 2))
        kf_f = (lambda x, *d: x.permute(*d))(kf_f, 1, 2, 0)
        y_f = kv_f * kf_f[None, :, :, :]
        y = (lambda x, s, axes=(-2, -1): torch.fft.irfft2(x, s=s, dim=axes).to(torch.bfloat16))(y_f, (1, L), axes=(1, 2))[:, 0, :S, :]
        y = y + kv * ssm_D[None, None, :]
        return q * y
    a = _A_ref(A_x, A_mem0, A_Wq, A_Wk, A_Wv, A_Wo, A_seg_len)
    b = _B_ref(B_q, B_k, B_v, B_shift_k, B_ssm_k, B_ssm_D)
    return torch.concatenate([a, b], axis=-1)
```

```cpp
#include <cuda_runtime.h>
#include <cuda_bf16.h>
#include <cuda.h>
#include <stdint.h>
#define DEVI __device__ __forceinline__
constexpr int SPIN_LIMIT = 1 << 22;

DEVI uint32_t smem_u32(const void* p) { return (uint32_t)__cvta_generic_to_shared(p); }
DEVI uint32_t mapa(uint32_t a, uint32_t rank) { uint32_t o; asm("mapa.shared::cluster.u32 %0,%1,%2;" : "=r"(o) : "r"(a), "r"(rank)); return o; }
DEVI void mbar_init(uint32_t b, uint32_t c) { asm volatile("mbarrier.init.shared::cta.b64 [%0],%1;" ::"r"(b), "r"(c) : "memory"); }
DEVI void mbar_expect(uint32_t b, uint32_t bytes) { asm volatile("mbarrier.arrive.expect_tx.shared::cta.b64 _,[%0],%1;" ::"r"(b), "r"(bytes) : "memory"); }
DEVI void mbar_arrive(uint32_t b) { asm volatile("mbarrier.arrive.shared::cta.b64 _,[%0];" ::"r"(b) : "memory"); }
DEVI bool mbar_try(uint32_t b, uint32_t ph) {
    uint32_t ok;
    asm volatile("{.reg .pred p; mbarrier.try_wait.parity.shared::cta.b64 p,[%1],%2; selp.u32 %0,1,0,p;}" : "=r"(ok) : "r"(b), "r"(ph) : "memory");
    return ok;
}
DEVI bool mbar_try_cl(uint32_t b, uint32_t ph) {
    uint32_t ok;
    asm volatile("{.reg .pred p; mbarrier.try_wait.parity.acquire.cluster.shared::cta.b64 p,[%1],%2; selp.u32 %0,1,0,p;}" : "=r"(ok) : "r"(b), "r"(ph) : "memory");
    return ok;
}
DEVI void mbar_wait(uint32_t b, uint32_t ph) { int g = 0; while (!mbar_try(b, ph)) { if (++g > SPIN_LIMIT) __trap(); } }
DEVI void mbar_wait_cl(uint32_t b, uint32_t ph) { int g = 0; while (!mbar_try_cl(b, ph)) { if (++g > SPIN_LIMIT) __trap(); } }
DEVI void bar_sync(int id, int n) { asm volatile("bar.sync %0,%1;" ::"r"(id), "r"(n) : "memory"); }
DEVI void bar_arrive(int id, int n) { asm volatile("bar.arrive %0,%1;" ::"r"(id), "r"(n) : "memory"); }
DEVI void cluster_arrive() { asm volatile("barrier.cluster.arrive.aligned;" ::: "memory"); }
DEVI void cluster_wait() { asm volatile("barrier.cluster.wait.aligned;" ::: "memory"); }
DEVI void fence_async_smem() { asm volatile("fence.proxy.async.shared::cta;" ::: "memory"); }
DEVI bool elect_one() {
    uint32_t p;
    asm volatile("{.reg .pred P; elect.sync _|P, 0xffffffff; selp.u32 %0,1,0,P;}" : "=r"(p));
    return p;
}
DEVI void ldsm4(uint32_t* r, uint32_t a) { asm volatile("ldmatrix.sync.aligned.m8n8.x4.shared.b16 {%0,%1,%2,%3},[%4];" : "=r"(r[0]), "=r"(r[1]), "=r"(r[2]), "=r"(r[3]) : "r"(a) : "memory"); }
DEVI void ldsm4t(uint32_t* r, uint32_t a) { asm volatile("ldmatrix.sync.aligned.m8n8.x4.trans.shared.b16 {%0,%1,%2,%3},[%4];" : "=r"(r[0]), "=r"(r[1]), "=r"(r[2]), "=r"(r[3]) : "r"(a) : "memory"); }
DEVI void ldsm2t(uint32_t* r, uint32_t a) { asm volatile("ldmatrix.sync.aligned.m8n8.x2.trans.shared.b16 {%0,%1},[%2];" : "=r"(r[0]), "=r"(r[1]) : "r"(a) : "memory"); }
DEVI void stsm4(uint32_t a, uint32_t r0, uint32_t r1, uint32_t r2, uint32_t r3) { asm volatile("stmatrix.sync.aligned.m8n8.x4.shared.b16 [%0],{%1,%2,%3,%4};" ::"r"(a), "r"(r0), "r"(r1), "r"(r2), "r"(r3) : "memory"); }
DEVI void stsm4t(uint32_t a, uint32_t r0, uint32_t r1, uint32_t r2, uint32_t r3) { asm volatile("stmatrix.sync.aligned.m8n8.x4.trans.shared.b16 [%0],{%1,%2,%3,%4};" ::"r"(a), "r"(r0), "r"(r1), "r"(r2), "r"(r3) : "memory"); }
DEVI void stsm2t(uint32_t a, uint32_t r0, uint32_t r1) { asm volatile("stmatrix.sync.aligned.m8n8.x2.trans.shared.b16 [%0],{%1,%2};" ::"r"(a), "r"(r0), "r"(r1) : "memory"); }
DEVI void mma16816(float* d, uint32_t a0, uint32_t a1, uint32_t a2, uint32_t a3, uint32_t b0, uint32_t b1) {
    asm volatile("mma.sync.aligned.m16n8k16.row.col.f32.bf16.bf16.f32 {%0,%1,%2,%3},{%4,%5,%6,%7},{%8,%9},{%0,%1,%2,%3};"
                 : "+f"(d[0]), "+f"(d[1]), "+f"(d[2]), "+f"(d[3]) : "r"(a0), "r"(a1), "r"(a2), "r"(a3), "r"(b0), "r"(b1));
}
DEVI uint32_t pack_bf16(float lo, float hi) { uint32_t r; asm("cvt.rn.bf16x2.f32 %0,%1,%2;" : "=r"(r) : "f"(hi), "f"(lo)); return r; }
DEVI uint4 lds128(uint32_t a) { uint4 v; asm volatile("ld.shared.v4.u32 {%0,%1,%2,%3},[%4];" : "=r"(v.x), "=r"(v.y), "=r"(v.z), "=r"(v.w) : "r"(a) : "memory"); return v; }
DEVI float2 lds64f(uint32_t a) { float2 v; asm volatile("ld.shared.v2.f32 {%0,%1},[%2];" : "=f"(v.x), "=f"(v.y) : "r"(a) : "memory"); return v; }
DEVI float4 lds128f(uint32_t a) { float4 v; asm volatile("ld.shared.v4.f32 {%0,%1,%2,%3},[%4];" : "=f"(v.x), "=f"(v.y), "=f"(v.z), "=f"(v.w) : "r"(a) : "memory"); return v; }
DEVI void sts128(uint32_t a, uint4 v) { asm volatile("st.shared.v4.u32 [%0],{%1,%2,%3,%4};" ::"r"(a), "r"(v.x), "r"(v.y), "r"(v.z), "r"(v.w) : "memory"); }
DEVI void sts32(uint32_t a, uint32_t v) { asm volatile("st.shared.u32 [%0],%1;" ::"r"(a), "r"(v) : "memory"); }
DEVI void st_async64f(uint32_t a, float x, float y, uint32_t bar) { asm volatile("st.async.weak.shared::cluster.mbarrier::complete_tx::bytes.v2.f32 [%0],{%1,%2},[%3];" ::"r"(a), "f"(x), "f"(y), "r"(bar) : "memory"); }
DEVI void st_async128f(uint32_t a, float x, float y, float z, float w, uint32_t bar) { asm volatile("st.async.weak.shared::cluster.mbarrier::complete_tx::bytes.v4.f32 [%0],{%1,%2,%3,%4},[%5];" ::"r"(a), "f"(x), "f"(y), "f"(z), "f"(w), "r"(bar) : "memory"); }
DEVI void st_async128(uint32_t a, uint4 v, uint32_t bar) { asm volatile("st.async.weak.shared::cluster.mbarrier::complete_tx::bytes.v4.b32 [%0],{%1,%2,%3,%4},[%5];" ::"r"(a), "r"(v.x), "r"(v.y), "r"(v.z), "r"(v.w), "r"(bar) : "memory"); }
DEVI uint4 ldg_relaxed128(const void* p) { uint4 v; asm volatile("ld.relaxed.gpu.global.v4.u32 {%0,%1,%2,%3},[%4];" : "=r"(v.x), "=r"(v.y), "=r"(v.z), "=r"(v.w) : "l"(p) : "memory"); return v; }
DEVI uint32_t ldg_relaxed32(const void* p) { uint32_t v; asm volatile("ld.relaxed.gpu.global.u32 %0,[%1];" : "=r"(v) : "l"(p) : "memory"); return v; }
DEVI void stg_relaxed32(void* p, uint32_t v) { asm volatile("st.relaxed.gpu.global.u32 [%0],%1;" ::"l"(p), "r"(v) : "memory"); }
DEVI void stg_relaxed128(void* p, uint32_t a, uint32_t b, uint32_t c, uint32_t d) { asm volatile("st.relaxed.gpu.global.v4.u32 [%0],{%1,%2,%3,%4};" ::"l"(p), "r"(a), "r"(b), "r"(c), "r"(d) : "memory"); }
DEVI uint4 ldg_nc128(const void* p) { uint4 v; asm volatile("ld.global.nc.L1::no_allocate.v4.u32 {%0,%1,%2,%3},[%4];" : "=r"(v.x), "=r"(v.y), "=r"(v.z), "=r"(v.w) : "l"(p)); return v; }
DEVI void tma2d(uint32_t dst, const CUtensorMap* tm, int c0, int c1, uint32_t bar) {
    asm volatile("cp.async.bulk.tensor.2d.shared::cluster.global.mbarrier::complete_tx::bytes [%0],[%1,{%2,%3}],[%4];" ::"r"(dst), "l"(tm), "r"(c0), "r"(c1), "r"(bar) : "memory");
}
DEVI void tma2d_mc(uint32_t dst, const CUtensorMap* tm, int c0, int c1, uint32_t bar, uint16_t mask) {
    asm volatile("cp.async.bulk.tensor.2d.shared::cluster.global.mbarrier::complete_tx::bytes.multicast::cluster [%0],[%1,{%2,%3}],[%4],%5;" ::"r"(dst), "l"(tm), "r"(c0), "r"(c1), "r"(bar), "h"(mask) : "memory");
}
DEVI void bulk_s2s(uint32_t dst, uint32_t src, uint32_t bytes, uint32_t bar) {
    asm volatile("cp.async.bulk.shared::cluster.shared::cta.mbarrier::complete_tx::bytes [%0],[%1],%2,[%3];" ::"r"(dst), "r"(src), "r"(bytes), "r"(bar) : "memory");
}
DEVI void bulk_s2g(void* dst, uint32_t src, uint32_t bytes) {
    asm volatile("cp.async.bulk.global.shared::cta.bulk_group [%0],[%1],%2;" ::"l"(dst), "r"(src), "r"(bytes) : "memory");
}
DEVI void bulk_commit() { asm volatile("cp.async.bulk.commit_group;" ::: "memory"); }
DEVI void bulk_wait_read0() { asm volatile("cp.async.bulk.wait_group.read 0;" ::: "memory"); }
DEVI void bulk_wait_read1() { asm volatile("cp.async.bulk.wait_group.read 1;" ::: "memory"); }
DEVI void bulk_wait0() { asm volatile("cp.async.bulk.wait_group 0;" ::: "memory"); }
DEVI void wg_fence() { asm volatile("wgmma.fence.sync.aligned;" ::: "memory"); }
DEVI void wg_commit() { asm volatile("wgmma.commit_group.sync.aligned;" ::: "memory"); }
template <int N> DEVI void wg_wait() { asm volatile("wgmma.wait_group.sync.aligned %0;" ::"n"(N) : "memory"); }
template <int ACC> DEVI void wgmma_rs_n32(float* d, const uint32_t* a, uint64_t desc) {
    asm volatile("wgmma.mma_async.sync.aligned.m64n32k16.f32.bf16.bf16 {%0,%1,%2,%3,%4,%5,%6,%7,%8,%9,%10,%11,%12,%13,%14,%15},{%16,%17,%18,%19},%20,%21,1,1,0;"
                 : "+f"(d[0]), "+f"(d[1]), "+f"(d[2]), "+f"(d[3]), "+f"(d[4]), "+f"(d[5]), "+f"(d[6]), "+f"(d[7]), "+f"(d[8]), "+f"(d[9]), "+f"(d[10]), "+f"(d[11]), "+f"(d[12]), "+f"(d[13]), "+f"(d[14]), "+f"(d[15])
                 : "r"(a[0]), "r"(a[1]), "r"(a[2]), "r"(a[3]), "l"(desc), "n"(ACC));
}
DEVI float ex2(float x) { float y; asm("ex2.approx.ftz.f32 %0,%1;" : "=f"(y) : "f"(x)); return y; }

DEVI void mma16816_h(float* d, uint32_t a0, uint32_t a2, uint32_t b0, uint32_t b1) {
    asm volatile("mma.sync.aligned.m16n8k16.row.col.f32.bf16.bf16.f32 {%0,%1,%2,%3},{%4,%4,%5,%5},{%6,%7},{%0,%1,%2,%3};"
                 : "+f"(d[0]), "+f"(d[1]), "+f"(d[2]), "+f"(d[3]) : "r"(a0), "r"(a2), "r"(b0), "r"(b1));
}
DEVI void mma1688(float* d, uint32_t a0, uint32_t a1, uint32_t b0) {
    asm volatile("mma.sync.aligned.m16n8k8.row.col.f32.bf16.bf16.f32 {%0,%1,%2,%3},{%4,%5},{%6},{%0,%1,%2,%3};"
                 : "+f"(d[0]), "+f"(d[1]), "+f"(d[2]), "+f"(d[3]) : "r"(a0), "r"(a1), "r"(b0));
}
DEVI void mma1688_h(float* d, uint32_t a0, uint32_t b0) {
    asm volatile("mma.sync.aligned.m16n8k8.row.col.f32.bf16.bf16.f32 {%0,%1,%2,%3},{%4,%4},{%5},{%0,%1,%2,%3};"
                 : "+f"(d[0]), "+f"(d[1]), "+f"(d[2]), "+f"(d[3]) : "r"(a0), "r"(b0));
}

constexpr int S_ = 2048, DM = 640, NH = 32, DH = 128, NSEG = 64;
constexpr int K1_THREADS = 384, K1_CTAS = 96;
constexpr uint32_t OFF_WO = 0, OFF_X = 57344, OFF_MEMS = 139264, OFF_V = 149504, OFF_QX = 169984, OFF_KX = 178176,
                   OFF_QM = 188416, OFF_S = 218624, OFF_OS = 223744, OFF_BAR = 225792;
constexpr uint32_t K1_SMEM = OFF_BAR + 256 + 1024;
constexpr uint32_t XBYTES = 40960, VBYTES = 10240, KXBYTES = 5120;
enum { BAR_W = 0, BAR_X0 = 8, BAR_S0 = 24, BAR_VX0 = 40, BAR_XF0 = 56 };
enum { NB_MAIN = 1, NB_MEM = 2, NB_PART = 3, NB_QK = 4, NB_O = 5, NB_HELP = 6, NB_EPI = 7 };

__device__ unsigned char g_scr_raw[4u << 20];
__device__ unsigned g_bar1;
__device__ int g_side[K1_CTAS];
__device__ __nv_bfloat16 g_ox[(size_t)S_ * 4096];
constexpr uint32_t QKV_IMG = 8192 + 2 * 5120 + 10240;
__device__ __align__(128) unsigned char g_qkv[(size_t)NSEG * NH * QKV_IMG];
#define TS(i)
#define TSB(i)
#define TSV(i, v)

DEVI int addr_par(const void* p) { return __popcll((unsigned long long)p & 0xB3000ull) & 1; }
DEVI uint32_t side_off(const char* scr, uint32_t ro, int sg, int k) { const int p = addr_par(scr + ro); return ro + (((p == sg) ? (k ? 3 : 0) : (k ? 2 : 1)) << 12); }

DEVI bool tag_ok(const uint4& v, uint32_t tag) { return (((v.x & v.y & v.z & v.w) & 1) == tag) & (((v.x | v.y | v.z | v.w) & 1) == tag); }
DEVI bool sent_ok(const uint4& v) { return (v.x != ~0u) & (v.y != ~0u) & (v.z != ~0u) & (v.w != ~0u); }

#define SIDE_AWARE 1
#define D1 300
#define D2 300
#define NPRE 4
struct K1Params {
    const __nv_bfloat16* mem0;
    const __nv_bfloat16* Wo;
};

__global__ void __launch_bounds__(K1_THREADS, 1)
k1_chain(const __grid_constant__ CUtensorMap tmX, const __grid_constant__ CUtensorMap tmWq,
         const __grid_constant__ CUtensorMap tmWk, const __grid_constant__ CUtensorMap tmWv, K1Params prm)
{
    extern __shared__ unsigned char smem_raw[];
    {
        const uint32_t bars0 = ((smem_u32(smem_raw) + 1023u) & ~1023u) + OFF_BAR;
        if (threadIdx.x == 0) {
            mbar_init(bars0 + BAR_W, 1);
            for (int i = 0; i < 2; i++) { mbar_init(bars0 + BAR_X0 + 8 * i, 1); mbar_init(bars0 + BAR_S0 + 8 * i, 1); mbar_init(bars0 + BAR_VX0 + 8 * i, 1); mbar_init(bars0 + BAR_XF0 + 8 * i, 3); }
            sts32(bars0 + 248, 0u);
            asm volatile("fence.mbarrier_init.release.cluster;" ::: "memory");
        }
        __syncthreads();
        cluster_arrive(); cluster_wait();
    }

    if (threadIdx.x < 256) {
        asm volatile("setmaxnreg.inc.sync.aligned.u32 216;");
        const int lane = __shfl_sync(~0u, (int)(threadIdx.x & 31), (int)(threadIdx.x & 31));
        const int warp = __shfl_sync(~0u, (int)(threadIdx.x >> 5), 0);
        const int tid = warp * 32 + lane;
        const int g = lane >> 2, t = lane & 3;
        const uint32_t sb = (smem_u32(smem_raw) + 1023u) & ~1023u, bars = sb + OFF_BAR;
        const int cta = blockIdx.x, h = cta / 3;
        uint32_t j; asm volatile("mov.u32 %0, %%cluster_ctarank;" : "=r"(j));
        char* const SCR = (char*)(((unsigned long long)g_scr_raw + 0x1FFFFFull) & ~0x1FFFFFull);
        const int t_begin = (j == 0) ? 0 : (j == 1 ? 14 : 27), t_cnt = (j == 0) ? 14 : 13;
        const int wg = warp >> 2, w = warp & 3;
        const int li = lane >> 3, lr = lane & 7;
        uint32_t a[160];
        mbar_wait(bars + BAR_W, 0);
        {
            const uint32_t base = sb + OFF_X + wg * 81920 + ((li >> 1) * 8 + lr) * 128 + (((2 * w + (li & 1)) ^ lr) << 4);
#pragma unroll
            for (int kk = 0; kk < 40; kk++) ldsm4t(&a[4 * kk], base + kk * 2048);
        }
        cluster_arrive(); cluster_wait();

        const bool has1 = (warp + 8 < t_cnt);
        uint32_t pp0, pp1;
        {
            const int pos = t * 4 + (g & 3), hf = g >> 2;
            const int u0 = (t_begin + warp) * 2 + hf, u1 = (t_begin + (has1 ? warp + 8 : warp)) * 2 + hf;
            pp0 = side_off(SCR, (u0 >> 1) * 16384, u0 & 1, h >> 4) + (h & 15) * 256 + pos * 16;
            pp1 = side_off(SCR, (u1 >> 1) * 16384, u1 & 1, h >> 4) + (h & 15) * 256 + pos * 16;
        }
        const uint64_t descX0 = (uint64_t)(((sb + OFF_X) & 0x3FFFF) >> 4) | (1ull << 16) | (64ull << 32) | (1ull << 62);
        const uint32_t l16 = sb + lane * 16;
        const uint32_t swz = ((2 * w + (li & 1)) ^ lr) << 4;
        const uint32_t st_m = (j < 2) ? sb + (wg ? OFF_KX + 32 * 128 : OFF_QM) + lr * 128 + swz
                                      : sb + OFF_V + (32 + lr) * 256 + wg * 128 + swz;
        const uint32_t st_m_par = (j < 2) ? (wg ? KXBYTES : 0) : VBYTES;
        const uint32_t st_x = (j < 2) ? sb + (wg ? OFF_KX : OFF_QX) + ((li >> 1) * 8 + lr) * 128 + swz
                                      : sb + OFF_V + ((li >> 1) * 8 + lr) * 256 + wg * 128 + swz;
        const uint32_t st_x_par = (j < 2) ? (wg ? KXBYTES : 4096) : VBYTES;
        const uint32_t st_x_q = (j < 2) ? 16 * 128 : 16 * 256;

        auto token_gemm = [&](int sg) {
            const int p = sg & 1;
            mbar_wait(bars + BAR_X0 + 8 * p, (sg >> 1) & 1);
            float d[16];
#pragma unroll
            for (int i = 0; i < 16; i++) d[i] = 0.f;
            const uint64_t dx = descX0 + (uint64_t)(p * (XBYTES >> 4));
            wg_fence();
            wgmma_rs_n32<0>(d, &a[0], dx);
#pragma unroll
            for (int kk = 1; kk < 40; kk++) wgmma_rs_n32<1>(d, &a[4 * kk], dx + (uint64_t)((kk >> 2) * 256 + (kk & 3) * 2));
            wg_commit();
            wg_wait<0>();
#pragma unroll
            for (int q = 0; q < 2; q++)
                stsm4t(st_x + p * st_x_par + q * st_x_q, pack_bf16(d[8 * q + 0], d[8 * q + 1]), pack_bf16(d[8 * q + 2], d[8 * q + 3]),
                       pack_bf16(d[8 * q + 4], d[8 * q + 5]), pack_bf16(d[8 * q + 6], d[8 * q + 7]));
            fence_async_smem();
            bar_arrive(NB_EPI, 288);
        };
        token_gemm(0);

#pragma unroll 1
        for (int s = 0; s < NSEG; s++) {
            const int p = s & 1, ph = (s >> 1) & 1;
            const bool last = (s == NSEG - 1);
            TS(7);
            bar_sync(NB_MEM, 384);
            TSB(0);
            {
                float c0[4] = {0.f, 0.f, 0.f, 0.f}, c1[4] = {0.f, 0.f, 0.f, 0.f}, c2[4] = {0.f, 0.f, 0.f, 0.f}, c3[4] = {0.f, 0.f, 0.f, 0.f};
                const uint32_t mb = l16 + OFF_MEMS;
#pragma unroll
                for (int kp = 0; kp < 20; kp += 2) {
                    uint32_t b[4], e[4];
                    ldsm4(b, mb + kp * 512);
                    ldsm4(e, mb + kp * 512 + 512);
                    mma16816(c0, a[8 * kp + 0], a[8 * kp + 1], a[8 * kp + 2], a[8 * kp + 3], b[0], b[1]);
                    mma16816(c1, a[8 * kp + 4], a[8 * kp + 5], a[8 * kp + 6], a[8 * kp + 7], b[2], b[3]);
                    mma16816(c2, a[8 * kp + 8], a[8 * kp + 9], a[8 * kp + 10], a[8 * kp + 11], e[0], e[1]);
                    mma16816(c3, a[8 * kp + 12], a[8 * kp + 13], a[8 * kp + 14], a[8 * kp + 15], e[2], e[3]);
                }
                stsm2t(st_m + p * st_m_par, pack_bf16((c0[0] + c1[0]) + (c2[0] + c3[0]), (c0[1] + c1[1]) + (c2[1] + c3[1])),
                       pack_bf16((c0[2] + c1[2]) + (c2[2] + c3[2]), (c0[3] + c1[3]) + (c2[3] + c3[3])));
            }
            TS(1);
            if (!last) {
                bar_arrive(NB_QK, 384);
                uint32_t wf[4 * NPRE];
#pragma unroll
                for (int kk = 0; kk < NPRE; kk++) ldsm4t(&wf[4 * kk], l16 + OFF_WO + warp * 4096 + kk * 512);
                bar_sync(NB_O, 384);
                TSB(4);
                const uint32_t tag = ph ^ 1, so = (uint32_t)p << 20;
                float e0[4] = {0.f, 0.f, 0.f, 0.f}, e1[4] = {0.f, 0.f, 0.f, 0.f}, f0[4] = {0.f, 0.f, 0.f, 0.f}, f1[4] = {0.f, 0.f, 0.f, 0.f};
#pragma unroll
                for (int q = 0; q < 4; q++) {
                    uint32_t ob[4];
                    ldsm4(ob, l16 + OFF_OS + q * 512);
                    if (2 * q + 1 < NPRE) {
                        mma16816(e0, wf[(8 * q + 0) % (4 * NPRE)], wf[(8 * q + 1) % (4 * NPRE)], wf[(8 * q + 2) % (4 * NPRE)], wf[(8 * q + 3) % (4 * NPRE)], ob[0], ob[1]);
                        mma16816(e1, wf[(8 * q + 4) % (4 * NPRE)], wf[(8 * q + 5) % (4 * NPRE)], wf[(8 * q + 6) % (4 * NPRE)], wf[(8 * q + 7) % (4 * NPRE)], ob[2], ob[3]);
                    } else {
                        uint32_t u0[4], u1[4];
                        ldsm4t(u0, l16 + OFF_WO + warp * 4096 + q * 1024);
                        ldsm4t(u1, l16 + OFF_WO + warp * 4096 + q * 1024 + 512);
                        mma16816(e0, u0[0], u0[1], u0[2], u0[3], ob[0], ob[1]);
                        mma16816(e1, u1[0], u1[1], u1[2], u1[3], ob[2], ob[3]);
                    }
                    if (has1) {
                        uint32_t w0[4], w1[4];
                        ldsm4t(w0, l16 + OFF_WO + (warp + 8) * 4096 + q * 1024);
                        ldsm4t(w1, l16 + OFF_WO + (warp + 8) * 4096 + q * 1024 + 512);
                        mma16816(f0, w0[0], w0[1], w0[2], w0[3], ob[0], ob[1]);
                        mma16816(f1, w1[0], w1[1], w1[2], w1[3], ob[2], ob[3]);
                    }
                }
                stg_relaxed128(SCR + (pp0 + so), (__float_as_uint(e0[0] + e1[0]) & ~1u) | tag, (__float_as_uint(e0[1] + e1[1]) & ~1u) | tag,
                               (__float_as_uint(e0[2] + e1[2]) & ~1u) | tag, (__float_as_uint(e0[3] + e1[3]) & ~1u) | tag);
                if (has1) stg_relaxed128(SCR + (pp1 + so), (__float_as_uint(f0[0] + f1[0]) & ~1u) | tag, (__float_as_uint(f0[1] + f1[1]) & ~1u) | tag,
                                         (__float_as_uint(f0[2] + f1[2]) & ~1u) | tag, (__float_as_uint(f0[3] + f1[3]) & ~1u) | tag);
                bar_arrive(NB_PART, 384);
                TS(5);
            }
            if (!last) token_gemm(s + 1);
            else { fence_async_smem(); bar_arrive(NB_MAIN, 288); }
            TS(6);
        }
        cluster_arrive(); cluster_wait();
    } else {
        asm volatile("setmaxnreg.dec.sync.aligned.u32 72;");
        const int lane = __shfl_sync(~0u, (int)(threadIdx.x & 31), (int)(threadIdx.x & 31));
        const int warp = __shfl_sync(~0u, (int)(threadIdx.x >> 5), 0);
        const int tid = warp * 32 + lane;
        const int g = lane >> 2, t = lane & 3;
        const uint32_t sb = (smem_u32(smem_raw) + 1023u) & ~1023u, bars = sb + OFF_BAR;
        const int cta = blockIdx.x, h = cta / 3;
        uint32_t j; asm volatile("mov.u32 %0, %%cluster_ctarank;" : "=r"(j));
        char* const SCR = (char*)(((unsigned long long)g_scr_raw + 0x1FFFFFull) & ~0x1FFFFFull);
        const int t_begin = (j == 0) ? 0 : (j == 1 ? 14 : 27), t_cnt = (j == 0) ? 14 : 13;
        const int ht = tid - 256, hw = warp - 8;
        const int li = lane >> 3, lr = lane & 7;
        if (hw == 0 && elect_one()) {
            mbar_expect(bars + BAR_W, 163840);
            const CUtensorMap* m0 = (j < 2) ? &tmWq : &tmWv;
            const CUtensorMap* m1 = (j < 2) ? &tmWk : &tmWv;
            const int c0 = h * 128 + ((j < 2) ? (int)j * 64 : 0), c1 = h * 128 + ((j < 2) ? (int)j * 64 : 64);
            for (int b = 0; b < 5; b++) {
                tma2d(sb + OFF_X + b * 16384, m0, c0, b * 128, bars + BAR_W);
                tma2d(sb + OFF_X + 81920 + b * 16384, m1, c1, b * 128, bars + BAR_W);
            }
        }
        __syncwarp();
        {
            if (cta < 80) { char* r = SCR + (size_t)(cta / 40) * 0x100000 + (cta % 40) * 16384; for (int i = ht; i < 1024; i += 128) stg_relaxed128(r + i * 16, 0u, 0u, 0u, 0u); }
            else if (cta < 88) { const int q = cta - 80, sl = q >> 1; char* r = SCR + 0xA0000 + (((sl & 1) << 15) | ((sl >> 1) << 18) | ((q & 1) << 14)); for (int i = ht; i < 1024; i += 128) stg_relaxed128(r + i * 16, ~0u, ~0u, ~0u, ~0u); }
            if (ht == 96) {
                int best0 = 1 << 30, best1 = 1 << 30;
                char* p0 = SCR + side_off(SCR, 0x1A0000, 0, 0) + (cta & 31) * 128;
                char* p1 = SCR + side_off(SCR, 0x1A0000, 1, 0) + (cta & 31) * 128;
                for (int r = 0; r < 5; r++) {
                    uint32_t v; int c0, c1;
                    asm volatile("mov.u32 %0, %%clock;" : "=r"(c0)::"memory");
                    asm volatile("atom.relaxed.gpu.global.add.u32 %0,[%1],1;" : "=r"(v) : "l"(p0) : "memory");
                    if (v == 0xdeadbeefu) __trap();
                    asm volatile("mov.u32 %0, %%clock;" : "=r"(c1)::"memory");
                    best0 = min(best0, c1 - c0);
                    asm volatile("mov.u32 %0, %%clock;" : "=r"(c0)::"memory");
                    asm volatile("atom.relaxed.gpu.global.add.u32 %0,[%1],1;" : "=r"(v) : "l"(p1) : "memory");
                    if (v == 0xdeadbeefu) __trap();
                    asm volatile("mov.u32 %0, %%clock;" : "=r"(c1)::"memory");
                    best1 = min(best1, c1 - c0);
                }
                stg_relaxed32(&g_side[cta], best1 < best0 ? 1u : 0u);
            }
            __threadfence();
            bar_sync(NB_HELP, 128);
        }
        unsigned bar_target = 0;
        if (ht == 0) { const unsigned old = atomicAdd(&g_bar1, 1u); bar_target = (old / K1_CTAS + 1) * K1_CTAS; }
        {
            const __nv_bfloat16* src = prm.Wo + (size_t)(h * 128 + ht) * DM + t_begin * 16;
            const uint32_t dst = sb + OFF_WO + (ht >> 4) * 512 + ((ht >> 3) & 1) * 256 + (ht & 7) * 16;
            for (int T0 = 0; T0 < t_cnt; T0 += 4) {
                uint4 x[4], y[4];
#pragma unroll
                for (int q = 0; q < 4; q++) { const int T = min(T0 + q, t_cnt - 1); x[q] = ldg_nc128(src + T * 16); y[q] = ldg_nc128(src + T * 16 + 8); }
#pragma unroll
                for (int q = 0; q < 4; q++) {
                    const int T = min(T0 + q, t_cnt - 1);
                    uint4 ev, od;
                    ev.x = __byte_perm(x[q].x, x[q].y, 0x5410); ev.y = __byte_perm(x[q].z, x[q].w, 0x5410); ev.z = __byte_perm(y[q].x, y[q].y, 0x5410); ev.w = __byte_perm(y[q].z, y[q].w, 0x5410);
                    od.x = __byte_perm(x[q].x, x[q].y, 0x7632); od.y = __byte_perm(x[q].z, x[q].w, 0x7632); od.z = __byte_perm(y[q].x, y[q].y, 0x7632); od.w = __byte_perm(y[q].z, y[q].w, 0x7632);
                    sts128(dst + T * 4096, ev);
                    sts128(dst + T * 4096 + 128, od);
                }
            }
        }
        if (ht == 0) { int gd = 0; while ((int)(ldg_relaxed32(&g_bar1) - bar_target) < 0) { if (++gd > SPIN_LIMIT) __trap(); } __threadfence(); }
        bar_sync(NB_HELP, 128);
        cluster_arrive(); cluster_wait();
        if (hw == 0 && elect_one()) {
            for (int p = 0; p < 2; p++) {
                mbar_expect(bars + BAR_X0 + 8 * p, XBYTES);
                for (int bx = j; bx < 10; bx += 3) tma2d_mc(sb + OFF_X + p * XBYTES + bx * 4096, &tmX, bx * 64, p * 32, bars + BAR_X0 + 8 * p, (uint16_t)7);
            }
        }
        __syncwarp();
        for (int i = 0; i < 5; i++) {
            const int ch = ht + 128 * i, u = ch >> 3, n = ch & 7;
            sts128(sb + OFF_MEMS + ch * 16, ldg_nc128(prm.mem0 + n * DM + u * 8));
        }
        int side, unit;
        {
            int n_side[2] = {0, 0}, rank = 0;
            side = (int)ldg_relaxed32(&g_side[cta]);
            for (int q = lane; q < K1_CTAS; q += 32) {
                const int sq = (int)ldg_relaxed32(&g_side[q]);
                n_side[0] += (sq == 0); n_side[1] += (sq == 1); rank += (sq == side && q < cta);
            }
            for (int o = 16; o; o >>= 1) { n_side[0] += __shfl_xor_sync(~0u, n_side[0], o); n_side[1] += __shfl_xor_sync(~0u, n_side[1], o); rank += __shfl_xor_sync(~0u, rank, o); }
            const int n_other = n_side[side ^ 1];
            if (rank < 40) unit = 2 * rank + side;
            else unit = (n_other + (rank - 40) < 40) ? 2 * (n_other + (rank - 40)) + (side ^ 1) : -1;
        }
        const bool red = unit >= 0;
        const int u = red ? unit : 0;
        const int rc = lane & 3, hg = lane >> 2;
        const uint32_t pbase_ = side_off(SCR, (u >> 1) * 16384, u & 1, hg >> 2) + ((hg * 4) & 15) * 256 + (hw * 4 + rc) * 16;
        uint32_t mo0_;
        {
            const int chunk = u * 8 + 2 * hw + ((lane >> 4) & 1), kb = chunk >> 8, off = (chunk & 255) * 16 + rc * 4;
            mo0_ = ((kb < 2) ? side_off(SCR, 0xA0000, 0, kb) : side_off(SCR, 0xA0000 + 16384, 0, 0)) + off;
        }
        const uint32_t mi0_ = side_off(SCR, 0xA0000, side, 0) + ht * 16;
        const uint32_t qaddr_ = sb + OFF_QM + lr * 128 + (((li >> 1) ^ lr) << 4);
        const uint32_t kaddr_ = sb + OFF_KX + (8 * hw + lr) * 128 + ((li ^ lr) << 4);
        const int c16a = 4 * hw + (li >> 1), c16m = 4 * hw + (li & 1);
        const uint32_t vxa_ = sb + OFF_V + ((li & 1) * 8 + lr) * 256 + (((c16a & 8) | ((c16a ^ lr) & 7)) << 4);
        const uint32_t vcm_ = sb + OFF_V + (32 + lr) * 256 + (((c16m & 8) | ((c16m ^ lr) & 7)) << 4);

        auto store_image = [&](int sg) {
            const int p = sg & 1;
            unsigned char* dst = g_qkv + (size_t)(sg * NH + h) * QKV_IMG;
            if (j < 2) {
                bulk_s2g(dst + j * 4096, sb + OFF_QX + p * 4096, 4096);
                bulk_s2g(dst + 8192 + j * KXBYTES, sb + OFF_KX + p * KXBYTES, KXBYTES);
            } else {
                bulk_s2g(dst + 8192 + 2 * KXBYTES, sb + OFF_V + p * VBYTES, VBYTES);
            }
            bulk_commit();
        };
        auto bulk_traffic = [&](int s) {
            const int p = s & 1;
            bar_sync(NB_EPI, 288);
            if (elect_one()) {
#pragma unroll
                for (int r3 = 0; r3 < 3; r3++) asm volatile("mbarrier.arrive.relaxed.cluster.shared::cluster.b64 _,[%0];" ::"r"(mapa(bars + BAR_XF0 + 8 * p, r3)) : "memory");
                if (j == 2 && s < NSEG - 1) {
                    bulk_s2s(mapa(sb + OFF_V + p * VBYTES, 0), sb + OFF_V + p * VBYTES, 8192, mapa(bars + BAR_VX0 + 8 * p, 0));
                    bulk_s2s(mapa(sb + OFF_V + p * VBYTES, 1), sb + OFF_V + p * VBYTES, 8192, mapa(bars + BAR_VX0 + 8 * p, 1));
                }
                if (s >= 1) store_image(s - 1);
                if (s + 2 < NSEG) {
                    mbar_wait(bars + BAR_XF0 + 8 * p, (s >> 1) & 1);
                    mbar_expect(bars + BAR_X0 + 8 * p, XBYTES);
                    for (int bx = j; bx < 10; bx += 3) tma2d_mc(sb + OFF_X + p * XBYTES + bx * 4096, &tmX, bx * 64, (s + 2) * 32, bars + BAR_X0 + 8 * p, (uint16_t)7);
                }
            }
            __syncwarp();
        };
        bar_arrive(NB_MEM, 384);
#pragma unroll 1
        for (int s = 0; s < NSEG - 1; s++) {
            const int p = s & 1, ph = (s >> 1) & 1;
            uint32_t qaddr = qaddr_, kaddr = kaddr_, vxa = vxa_, vcm = vcm_, pbase = pbase_, mo0 = mo0_, mi0 = mi0_, l8 = lane * 8;
            asm volatile("" : "+r"(qaddr), "+r"(kaddr), "+r"(vxa), "+r"(vcm), "+r"(pbase), "+r"(mo0), "+r"(mi0), "+r"(l8));
            const uint32_t sdst = sb + OFF_S + j * 1280 + l8;
            TS(8);
            if (ht == 0) {
                mbar_expect(bars + BAR_S0 + 8 * p, j < 2 ? 4608 : 2560);
                if (j < 2) mbar_expect(bars + BAR_VX0 + 8 * p, 8192);
            }
            if (hw == 2) bulk_traffic(s);
            const uint32_t sbar = bars + BAR_S0 + 8 * p;
            if (j < 2) {
                uint32_t ka[4], kb[4];
                ldsm4(ka, kaddr + p * KXBYTES);
                ldsm4(kb, (kaddr + p * KXBYTES) ^ 64);
                bar_sync(NB_QK, 384);
                TSB(9);
                uint32_t q0[4], q1[4], q2[4], q3[4];
                ldsm4(q0, qaddr); ldsm4(q2, qaddr ^ 64); ldsm4(q1, qaddr ^ 32); ldsm4(q3, qaddr ^ 96);
                float s0[4] = {0.f, 0.f, 0.f, 0.f}, s1[4] = {0.f, 0.f, 0.f, 0.f};
                mma16816(s0, q0[0], q0[1], q0[2], q0[3], ka[0], ka[1]);
                mma16816(s1, q2[0], q2[1], q2[2], q2[3], kb[0], kb[1]);
                if (hw == 0) { uint32_t km = kaddr + p * KXBYTES + 32 * 128; uint32_t kc[4], kd[4]; ldsm4(kc, km); ldsm4(kd, km ^ 64);
                    float m0[4] = {0.f, 0.f, 0.f, 0.f}, m1[4] = {0.f, 0.f, 0.f, 0.f};
                    mma16816(m0, q0[0], q0[1], q0[2], q0[3], kc[0], kc[1]);
                    mma16816(m1, q2[0], q2[1], q2[2], q2[3], kd[0], kd[1]);
                    mma16816(m0, q1[0], q1[1], q1[2], q1[3], kc[2], kc[3]);
                    mma16816(m1, q3[0], q3[1], q3[2], q3[3], kd[2], kd[3]);
                    const uint32_t d4 = sdst + p * 2560 + 4 * 256;
#pragma unroll
                    for (int r3 = 0; r3 < 3; r3++) st_async64f(mapa(d4, r3), m0[0] + m1[0], m0[1] + m1[1], mapa(sbar, r3));
                }
                mma16816(s0, q1[0], q1[1], q1[2], q1[3], ka[2], ka[3]);
                mma16816(s1, q3[0], q3[1], q3[2], q3[3], kb[2], kb[3]);
                const uint32_t d0 = sdst + p * 2560 + hw * 256;
#pragma unroll
                for (int r3 = 0; r3 < 3; r3++) st_async64f(mapa(d0, r3), s0[0] + s1[0], s0[1] + s1[1], mapa(sbar, r3));
            } else {
                bar_sync(NB_QK, 384);
                TSB(9);
                const uint32_t src = sb + OFF_V + p * VBYTES + 32 * 256 + ht * 16;
                const uint4 v = lds128(src);
                st_async128(mapa(src, 0), v, mapa(sbar, 0));
                st_async128(mapa(src, 1), v, mapa(sbar, 1));
            }
            TS(14);
            uint32_t va[4], vb[4], vc[4], vd[4];
            if (j < 2) mbar_wait(bars + BAR_VX0 + 8 * p, ph);
            {
                const uint32_t b0 = vxa + p * VBYTES, b1 = (vxa ^ 0x20) + p * VBYTES;
                ldsm4t(va, b0); ldsm4t(vb, b0 + 16 * 256);
                ldsm4t(vc, b1); ldsm4t(vd, b1 + 16 * 256);
            }
            mbar_wait(sbar, ph);
            TS(15);
            {
                float sc[10];
                const uint32_t sa = sb + OFF_S + p * 2560 + l8;
                const float sl2 = 0.08838834764831845f * 1.4426950408889634f;
#pragma unroll
                for (int nj = 0; nj < 5; nj++) {
                    const float2 x = lds64f(sa + nj * 256), y = lds64f(sa + 1280 + nj * 256);
                    sc[2 * nj] = x.x + y.x; sc[2 * nj + 1] = x.y + y.y;
                }
                uint32_t vm0[2], vm1[2];
                ldsm2t(vm0, vcm + p * VBYTES); ldsm2t(vm1, (vcm + p * VBYTES) ^ 0x20);
                float m = fmaxf(fmaxf(fmaxf(sc[0], sc[1]), fmaxf(sc[2], sc[3])), fmaxf(fmaxf(sc[4], sc[5]), fmaxf(sc[6], sc[7])));
                m = fmaxf(m, fmaxf(sc[8], sc[9]));
                m = fmaxf(m, __shfl_xor_sync(~0u, m, 1));
                m = fmaxf(m, __shfl_xor_sync(~0u, m, 2));
                const float ms = m * sl2;
                uint32_t pp[5];
#pragma unroll
                for (int nj = 0; nj < 5; nj++) pp[nj] = pack_bf16(ex2(fmaf(sc[2 * nj], sl2, -ms)), ex2(fmaf(sc[2 * nj + 1], sl2, -ms)));
                const uint32_t one2 = 0x3F803F80u;
                float o0[4] = {0.f, 0.f, 0.f, 0.f}, o1[4] = {0.f, 0.f, 0.f, 0.f}, o2[4] = {0.f, 0.f, 0.f, 0.f}, o3[4] = {0.f, 0.f, 0.f, 0.f}, su[4] = {0.f, 0.f, 0.f, 0.f};
                mma16816_h(su, pp[0], pp[1], one2, one2);
                mma16816_h(o0, pp[0], pp[1], va[0], va[1]);
                mma16816_h(o1, pp[0], pp[1], va[2], va[3]);
                mma16816_h(o2, pp[0], pp[1], vc[0], vc[1]);
                mma16816_h(o3, pp[0], pp[1], vc[2], vc[3]);
                mma16816_h(su, pp[2], pp[3], one2, one2);
                mma16816_h(o0, pp[2], pp[3], vb[0], vb[1]);
                mma16816_h(o1, pp[2], pp[3], vb[2], vb[3]);
                mma16816_h(o2, pp[2], pp[3], vd[0], vd[1]);
                mma16816_h(o3, pp[2], pp[3], vd[2], vd[3]);
                mma1688_h(su, pp[4], one2);
                mma1688_h(o0, pp[4], vm0[0]);
                mma1688_h(o1, pp[4], vm0[1]);
                mma1688_h(o2, pp[4], vm1[0]);
                mma1688_h(o3, pp[4], vm1[1]);
                const float inv = __fdividef(1.f, su[0]);
                const uint32_t oa = sb + OFF_OS + hw * 512 + lane * 4 + (g * 12 - g * 12);
                const uint32_t ob = sb + OFF_OS + hw * 512 + g * 16 + t * 4;
                (void)oa;
                sts32(ob, pack_bf16(o0[0] * inv, o0[1] * inv));
                sts32(ob + 128, pack_bf16(o1[0] * inv, o1[1] * inv));
                sts32(ob + 256, pack_bf16(o2[0] * inv, o2[1] * inv));
                sts32(ob + 384, pack_bf16(o3[0] * inv, o3[1] * inv));
            }
            if (hw == 2 && lane == 0) bulk_wait_read0();
            __syncwarp();
            bar_arrive(NB_O, 384);
            TS(16);
            bar_sync(NB_PART, 384);
            TSB(10);
            const int nsl = (s + 1) & 3, rsl = (s + 3) & 3;
            const uint32_t nso = ((nsl & 1) << 15) | ((nsl >> 1) << 18), rso = ((rsl & 1) << 15) | ((rsl >> 1) << 18);
            { uint32_t z_; asm volatile("ld.volatile.shared.u32 %0,[%1];" : "=r"(z_) : "r"(sb + OFF_BAR + 248) : "memory"); if (z_ == 0x12345678u) __trap(); }
            int tclk; asm volatile("mov.u32 %0, %%clock;" : "=r"(tclk)::"memory");
            if (red) {
                const uint32_t tag = ph ^ 1;
                if (D1 > 0) { int c; do { asm volatile("mov.u32 %0, %%clock;" : "=r"(c)::"memory"); } while (c - tclk < D1); }
                const char* b = SCR + (pbase + ((uint32_t)p << 20));
                TS(19);
                uint4 v0 = ldg_relaxed128(b), v1 = ldg_relaxed128(b + 256), v2 = ldg_relaxed128(b + 512), v3 = ldg_relaxed128(b + 768);
                int gd = 0;
                while (true) {
                    const bool k0 = tag_ok(v0, tag), k1 = tag_ok(v1, tag), k2 = tag_ok(v2, tag), k3 = tag_ok(v3, tag);
                    if (__all_sync(~0u, k0 & k1 & k2 & k3)) break;
                    if (!k0) v0 = ldg_relaxed128(b);
                    if (!k1) v1 = ldg_relaxed128(b + 256);
                    if (!k2) v2 = ldg_relaxed128(b + 512);
                    if (!k3) v3 = ldg_relaxed128(b + 768);
                    if (++gd > SPIN_LIMIT) __trap();
                }
                TS(11);
                TSV(17, gd);
                const float a0 = (__uint_as_float(v0.x) + __uint_as_float(v1.x)) + (__uint_as_float(v2.x) + __uint_as_float(v3.x));
                const float a1 = (__uint_as_float(v0.y) + __uint_as_float(v1.y)) + (__uint_as_float(v2.y) + __uint_as_float(v3.y));
                const float a2 = (__uint_as_float(v0.z) + __uint_as_float(v1.z)) + (__uint_as_float(v2.z) + __uint_as_float(v3.z));
                const float a3 = (__uint_as_float(v0.w) + __uint_as_float(v1.w)) + (__uint_as_float(v2.w) + __uint_as_float(v3.w));
                const bool up = lane & 16;
                float k0f = up ? a1 : a0, k1f = up ? a3 : a2;
                k0f += __shfl_xor_sync(~0u, up ? a0 : a1, 16); k1f += __shfl_xor_sync(~0u, up ? a2 : a3, 16);
                k0f += __shfl_xor_sync(~0u, k0f, 8); k1f += __shfl_xor_sync(~0u, k1f, 8);
                k0f += __shfl_xor_sync(~0u, k0f, 4); k1f += __shfl_xor_sync(~0u, k1f, 4);
                const uint32_t wv = pack_bf16(k0f, k1f);
                if ((lane & 12) == 0) { stg_relaxed32(SCR + (mo0 + nso), wv); stg_relaxed32(SCR + ((mo0 ^ 0x1000u) + nso), wv); }
            }
            TS(12);
            if (red) { if (D2 > 0) { asm volatile("mov.u32 %0, %%clock;" : "=r"(tclk)::"memory"); int c; do { asm volatile("mov.u32 %0, %%clock;" : "=r"(c)::"memory"); } while (c - tclk < D2); } }
            else { int c; do { asm volatile("mov.u32 %0, %%clock;" : "=r"(c)::"memory"); } while (c - tclk < D1 + 700 + D2); }
            {
                const char* ma = SCR + (mi0 + nso); const char* mb = SCR + ((mi0 ^ 0x3000u) + nso);
                TS(2);
                uint4 v0 = ldg_relaxed128(ma), v1 = ldg_relaxed128(ma + 2048), v2 = ldg_relaxed128(mb), v3 = ldg_relaxed128(mb + 2048), v4 = ldg_relaxed128(ma + 0x4000);
                int gd = 0;
                while (true) {
                    const bool k0 = sent_ok(v0), k1 = sent_ok(v1), k2 = sent_ok(v2), k3 = sent_ok(v3), k4 = sent_ok(v4);
                    if (k0 & k1 & k2 & k3 & k4) break;
                    if (!k0) v0 = ldg_relaxed128(ma);
                    if (!k1) v1 = ldg_relaxed128(ma + 2048);
                    if (!k2) v2 = ldg_relaxed128(mb);
                    if (!k3) v3 = ldg_relaxed128(mb + 2048);
                    if (!k4) v4 = ldg_relaxed128(ma + 0x4000);
                    if (++gd > SPIN_LIMIT) __trap();
                }
                TS(3);
                TSV(18, gd);
                const uint32_t md = sb + OFF_MEMS + ht * 16;
                sts128(md, v0); sts128(md + 2048, v1); sts128(md + 4096, v2); sts128(md + 6144, v3); sts128(md + 8192, v4);
            }
            bar_arrive(NB_MEM, 384);
            TS(13);
            if (red && (lane & 12) == 0) { stg_relaxed32(SCR + (mo0 + rso), ~0u); stg_relaxed32(SCR + ((mo0 ^ 0x1000u) + rso), ~0u); }
        }
        if (hw == 2) {
            bulk_traffic(NSEG - 1);
            bar_sync(NB_MAIN, 288);
            if (elect_one()) { store_image(NSEG - 1); bulk_wait0(); }
            __syncwarp();
        }
        cluster_arrive(); cluster_wait();
    }
}

DEVI void bulk_g2s(uint32_t dst, const void* src, uint32_t bytes, uint32_t bar) {
    asm volatile("cp.async.bulk.shared::cluster.global.mbarrier::complete_tx::bytes [%0],[%1],%2,[%3];" ::"r"(dst), "l"(src), "r"(bytes), "r"(bar) : "memory");
}
DEVI void attn_warp(uint32_t img, uint32_t ost, int mi, int lane, __nv_bfloat16* orow  ) {
    const int li = lane >> 3, lr = lane & 7, g = lane >> 2, t = lane & 3;
    float sc[5][4];
#pragma unroll
    for (int nj = 0; nj < 5; nj++) { sc[nj][0] = sc[nj][1] = sc[nj][2] = sc[nj][3] = 0.f; }
#pragma unroll
    for (int hf = 0; hf < 2; hf++) {
#pragma unroll
        for (int kp = 0; kp < 2; kp++) {
            uint32_t a0[4], a1[4];
            const uint32_t qrow = img + hf * 4096 + (16 * mi + (li & 1) * 8 + lr) * 128;
            ldsm4(a0, qrow + (((4 * kp + (li >> 1)) ^ lr) << 4));
            ldsm4(a1, qrow + (((4 * kp + 2 + (li >> 1)) ^ lr) << 4));
#pragma unroll
            for (int nj = 0; nj < 5; nj++) {
                uint32_t b[4];
                ldsm4(b, img + 8192 + hf * 5120 + (8 * nj + lr) * 128 + (((4 * kp + li) ^ lr) << 4));
                mma16816(sc[nj], a0[0], a0[1], a0[2], a0[3], b[0], b[1]);
                mma16816(sc[nj], a1[0], a1[1], a1[2], a1[3], b[2], b[3]);
            }
        }
    }
    const float sl2 = 0.08838834764831845f * 1.4426950408889634f;
    const int i0 = 16 * mi + g, i1 = i0 + 8;
    float m0 = -1e30f, m1 = -1e30f;
#pragma unroll
    for (int nj = 0; nj < 5; nj++) {
        const int key = 8 * nj + 2 * t;
        if (nj < 4) {
            if (key > i0) sc[nj][0] = -1e30f;
            if (key + 1 > i0) sc[nj][1] = -1e30f;
            if (key > i1) sc[nj][2] = -1e30f;
            if (key + 1 > i1) sc[nj][3] = -1e30f;
        }
        m0 = fmaxf(m0, fmaxf(sc[nj][0], sc[nj][1])); m1 = fmaxf(m1, fmaxf(sc[nj][2], sc[nj][3]));
    }
    m0 = fmaxf(m0, __shfl_xor_sync(~0u, m0, 1)); m1 = fmaxf(m1, __shfl_xor_sync(~0u, m1, 1));
    m0 = fmaxf(m0, __shfl_xor_sync(~0u, m0, 2)); m1 = fmaxf(m1, __shfl_xor_sync(~0u, m1, 2));
    m0 *= sl2; m1 *= sl2;
    float u0 = 0.f, u1 = 0.f;
#pragma unroll
    for (int nj = 0; nj < 5; nj++) {
        sc[nj][0] = ex2(fmaf(sc[nj][0], sl2, -m0)); sc[nj][1] = ex2(fmaf(sc[nj][1], sl2, -m0)); u0 += sc[nj][0] + sc[nj][1];
        sc[nj][2] = ex2(fmaf(sc[nj][2], sl2, -m1)); sc[nj][3] = ex2(fmaf(sc[nj][3], sl2, -m1)); u1 += sc[nj][2] + sc[nj][3];
    }
    u0 += __shfl_xor_sync(~0u, u0, 1); u1 += __shfl_xor_sync(~0u, u1, 1);
    u0 += __shfl_xor_sync(~0u, u0, 2); u1 += __shfl_xor_sync(~0u, u1, 2);
    u0 = __fdividef(1.f, u0); u1 = __fdividef(1.f, u1);
    uint32_t pa[10];
#pragma unroll
    for (int nj = 0; nj < 5; nj++) { pa[2 * nj] = pack_bf16(sc[nj][0] * u0, sc[nj][1] * u0); pa[2 * nj + 1] = pack_bf16(sc[nj][2] * u1, sc[nj][3] * u1); }
    const uint32_t vimg = img + 8192 + 10240;
#pragma unroll 2
    for (int dg = 0; dg < 8; dg++) {
        const int c16 = 2 * dg + (li >> 1), c16b = 2 * dg + (li & 1);
        const uint32_t vb = vimg + ((li & 1) * 8 + lr) * 256 + (((c16 & 8) | ((c16 ^ lr) & 7)) << 4);
        uint32_t v0[4], v1[4], v2[2];
        ldsm4t(v0, vb); ldsm4t(v1, vb + 16 * 256);
        ldsm2t(v2, vimg + (32 + lr) * 256 + (((c16b & 8) | ((c16b ^ lr) & 7)) << 4));
        float o0[4] = {0.f, 0.f, 0.f, 0.f}, o1[4] = {0.f, 0.f, 0.f, 0.f};
        mma16816(o0, pa[0], pa[1], pa[2], pa[3], v0[0], v0[1]);
        mma16816(o1, pa[0], pa[1], pa[2], pa[3], v0[2], v0[3]);
        mma16816(o0, pa[4], pa[5], pa[6], pa[7], v1[0], v1[1]);
        mma16816(o1, pa[4], pa[5], pa[6], pa[7], v1[2], v1[3]);
        mma1688(o0, pa[8], pa[9], v2[0]);
        mma1688(o1, pa[8], pa[9], v2[1]);
        stsm4(ost + ((li & 1) * 8 + lr) * 272 + (2 * dg + (li >> 1)) * 16,
              pack_bf16(o0[0], o0[1]), pack_bf16(o0[2], o0[3]), pack_bf16(o1[0], o1[1]), pack_bf16(o1[2], o1[3]));
    }
    __syncwarp();
#pragma unroll
    for (int q = 0; q < 8; q++) {
        const int row = 2 * q + (lane >> 4), ch = lane & 15;
        *(uint4*)(orow + (size_t)row * 4096 + ch * 8) = lds128(ost + row * 272 + ch * 16);
    }
    __syncwarp();
}

constexpr uint32_t K2A_SMEM = 4 * QKV_IMG + 8 * 16 * 272 + 64 + 128;
__global__ void __launch_bounds__(256) k2a_attn() {
    extern __shared__ unsigned char smem_raw[];
    const uint32_t sb = (smem_u32(smem_raw) + 127u) & ~127u;
    const int warp = threadIdx.x >> 5, lane = threadIdx.x & 31;
    const uint32_t bar = sb + 4 * QKV_IMG + 8 * 16 * 272;
    if (threadIdx.x == 0) { mbar_init(bar, 1); asm volatile("fence.mbarrier_init.release.cluster;" ::: "memory"); fence_async_smem();
        mbar_expect(bar, 4 * QKV_IMG);
        bulk_g2s(sb, g_qkv + (size_t)blockIdx.x * 4 * QKV_IMG, 4 * QKV_IMG, bar); }
    __syncthreads();
    mbar_wait(bar, 0);
    const int item = blockIdx.x * 4 + (warp >> 1), seg = item >> 5, h = item & 31, mi = warp & 1;
    attn_warp(sb + (warp >> 1) * QKV_IMG, sb + 4 * QKV_IMG + warp * 16 * 272, mi, lane, g_ox + (size_t)(seg * 32 + 16 * mi) * 4096 + h * 128);
}

template <int ACC> DEVI void wgmma_ss_n128_tb(float* d, uint64_t da, uint64_t db) {
    asm volatile("wgmma.mma_async.sync.aligned.m64n128k16.f32.bf16.bf16 "
        "{%0,%1,%2,%3,%4,%5,%6,%7,%8,%9,%10,%11,%12,%13,%14,%15,%16,%17,%18,%19,%20,%21,%22,%23,%24,%25,%26,%27,%28,%29,%30,%31,"
        "%32,%33,%34,%35,%36,%37,%38,%39,%40,%41,%42,%43,%44,%45,%46,%47,%48,%49,%50,%51,%52,%53,%54,%55,%56,%57,%58,%59,%60,%61,%62,%63},%64,%65,%66,1,1,0,1;"
        : "+f"(d[0]), "+f"(d[1]), "+f"(d[2]), "+f"(d[3]), "+f"(d[4]), "+f"(d[5]), "+f"(d[6]), "+f"(d[7]), "+f"(d[8]), "+f"(d[9]), "+f"(d[10]), "+f"(d[11]), "+f"(d[12]), "+f"(d[13]), "+f"(d[14]), "+f"(d[15]),
          "+f"(d[16]), "+f"(d[17]), "+f"(d[18]), "+f"(d[19]), "+f"(d[20]), "+f"(d[21]), "+f"(d[22]), "+f"(d[23]), "+f"(d[24]), "+f"(d[25]), "+f"(d[26]), "+f"(d[27]), "+f"(d[28]), "+f"(d[29]), "+f"(d[30]), "+f"(d[31]),
          "+f"(d[32]), "+f"(d[33]), "+f"(d[34]), "+f"(d[35]), "+f"(d[36]), "+f"(d[37]), "+f"(d[38]), "+f"(d[39]), "+f"(d[40]), "+f"(d[41]), "+f"(d[42]), "+f"(d[43]), "+f"(d[44]), "+f"(d[45]), "+f"(d[46]), "+f"(d[47]),
          "+f"(d[48]), "+f"(d[49]), "+f"(d[50]), "+f"(d[51]), "+f"(d[52]), "+f"(d[53]), "+f"(d[54]), "+f"(d[55]), "+f"(d[56]), "+f"(d[57]), "+f"(d[58]), "+f"(d[59]), "+f"(d[60]), "+f"(d[61]), "+f"(d[62]), "+f"(d[63])
        : "l"(da), "l"(db), "n"(ACC));
}
constexpr int GB_STAGES = 6;
constexpr uint32_t GB_STAGE_BYTES = 16384 + 16384;
constexpr uint32_t K2B_SMEM = GB_STAGES * GB_STAGE_BYTES + 256 + 1024;
__global__ void __launch_bounds__(384, 1) k2b_outproj(const __grid_constant__ CUtensorMap tmO, const __grid_constant__ CUtensorMap tmWo, __nv_bfloat16* out) {
    extern __shared__ unsigned char smem_raw[];
    const uint32_t sb = (smem_u32(smem_raw) + 1023u) & ~1023u;
    const uint32_t full = sb + GB_STAGES * GB_STAGE_BYTES, empty = full + 8 * GB_STAGES;
    const int warp = threadIdx.x >> 5, lane = threadIdx.x & 31;
    const int mt = blockIdx.x / 5, nt = blockIdx.x % 5;
    if (threadIdx.x == 0) { for (int i = 0; i < GB_STAGES; i++) { mbar_init(full + 8 * i, 1); mbar_init(empty + 8 * i, 2); } asm volatile("fence.mbarrier_init.release.cluster;" ::: "memory"); }
    __syncthreads();
    if (warp >= 8) {
        if (warp == 8 && elect_one()) {
            for (int kt = 0; kt < 64; kt++) {
                const int st = kt % GB_STAGES, it = kt / GB_STAGES;
                if (it > 0) mbar_wait(empty + 8 * st, (it - 1) & 1);
                mbar_expect(full + 8 * st, GB_STAGE_BYTES);
                const uint32_t a = sb + st * GB_STAGE_BYTES;
                tma2d(a, &tmO, kt * 64, mt * 128, full + 8 * st);
                tma2d(a + 16384, &tmWo, nt * 128, kt * 64, full + 8 * st);
                tma2d(a + 16384 + 8192, &tmWo, nt * 128 + 64, kt * 64, full + 8 * st);
            }
        }
    } else {
        const int wg = warp >> 2;
        float d[64];
#pragma unroll
        for (int i = 0; i < 64; i++) d[i] = 0.f;
        for (int kt = 0; kt < 64; kt++) {
            const int st = kt % GB_STAGES, it = kt / GB_STAGES;
            mbar_wait(full + 8 * st, it & 1);
            const uint32_t a = sb + st * GB_STAGE_BYTES + wg * 8192, b = sb + st * GB_STAGE_BYTES + 16384;
            const uint64_t da = (uint64_t)((a & 0x3FFFF) >> 4) | (1ull << 16) | (64ull << 32) | (1ull << 62);
            const uint64_t db = (uint64_t)((b & 0x3FFFF) >> 4) | (512ull << 16) | (64ull << 32) | (1ull << 62);
            wg_fence();
#pragma unroll
            for (int k = 0; k < 4; k++) wgmma_ss_n128_tb<1>(d, da + 2 * k, db + 128 * k);
            wg_commit();
            wg_wait<1>();
            if (kt > 0 && (threadIdx.x & 127) == 0) mbar_arrive(empty + 8 * ((kt - 1) % GB_STAGES));
        }
        wg_wait<0>();
        const int g = lane >> 2, t = lane & 3, w = warp & 3;
        const int row0 = mt * 128 + wg * 64 + w * 16 + g;
#pragma unroll
        for (int n = 0; n < 16; n++) {
            const int col = nt * 128 + 8 * n + 2 * t;
            *(uint32_t*)(out + (size_t)row0 * 1280 + col) = pack_bf16(d[4 * n], d[4 * n + 1]);
            *(uint32_t*)(out + (size_t)(row0 + 8) * 1280 + col) = pack_bf16(d[4 * n + 2], d[4 * n + 3]);
        }
    }
}

constexpr uint32_t CB_U_BYTES = 40 * 128;
constexpr uint32_t CB_K_COPY = (2048 + 64 + 16) * 2;
constexpr uint32_t CB_K_BYTES = 2 * CB_K_COPY + 64;
constexpr uint32_t K2C_SMEM = 8 * (CB_U_BYTES + CB_K_BYTES) + 128;
DEVI float bf2f(uint32_t lo16) { return __uint_as_float(lo16 << 16); }
DEVI float rbf(float x) { return __bfloat162float(__float2bfloat16_rn(x)); }
__global__ void __launch_bounds__(256) k2c_conv(const __nv_bfloat16* __restrict__ q, const __nv_bfloat16* __restrict__ k, const __nv_bfloat16* __restrict__ v,
                                                const __nv_bfloat16* __restrict__ shk, const __nv_bfloat16* __restrict__ ssk, const __nv_bfloat16* __restrict__ ssD,
                                                __nv_bfloat16* __restrict__ out) {
    extern __shared__ unsigned char smem_raw[];
    const uint32_t sb = (smem_u32(smem_raw) + 127u) & ~127u;
    const uint32_t U0 = sb, K0 = sb + 8 * CB_U_BYTES;
    const int tid = threadIdx.x, warp = tid >> 5, lane = tid & 31;
    const int c0 = blockIdx.x * 8;
    for (int i = tid; i < 8 * 64; i += 256) sts128(U0 + (i >> 6) * CB_U_BYTES + (i & 63) * 16, make_uint4(0, 0, 0, 0));
    {
        float w[8][4];
        const int t0 = tid * 8;
        uint32_t wk[8][2];
#pragma unroll
        for (int c = 0; c < 8; c++) { const uint2 x = *(const uint2*)(shk + (c0 + c) * 4); wk[c][0] = x.x; wk[c][1] = x.y; }
#pragma unroll
        for (int c = 0; c < 8; c++) { w[c][0] = bf2f(wk[c][0] & 0xffff); w[c][1] = bf2f(wk[c][0] >> 16); w[c][2] = bf2f(wk[c][1] & 0xffff); w[c][3] = bf2f(wk[c][1] >> 16); }
        float kp[3][8];
#pragma unroll
        for (int r = 0; r < 3; r++) {
            uint4 x = make_uint4(0, 0, 0, 0);
            if (t0 - 3 + r >= 0) x = ldg_nc128(k + (size_t)(t0 - 3 + r) * DM + c0);
            const uint32_t xx[4] = {x.x, x.y, x.z, x.w};
#pragma unroll
            for (int c = 0; c < 8; c++) kp[r][c] = bf2f((xx[c >> 1] >> ((c & 1) * 16)) & 0xffff);
        }
        uint32_t u[8][4];
#pragma unroll
        for (int tt = 0; tt < 8; tt++) {
            const uint4 x = ldg_nc128(k + (size_t)(t0 + tt) * DM + c0), y = ldg_nc128(v + (size_t)(t0 + tt) * DM + c0);
            const uint32_t xx[4] = {x.x, x.y, x.z, x.w}, yy[4] = {y.x, y.y, y.z, y.w};
#pragma unroll
            for (int c = 0; c < 8; c++) {
                const float kc = bf2f((xx[c >> 1] >> ((c & 1) * 16)) & 0xffff), vc = bf2f((yy[c >> 1] >> ((c & 1) * 16)) & 0xffff);
                float acc = rbf(kp[0][c] * w[c][3]);
                acc = rbf(acc + rbf(kp[1][c] * w[c][2]));
                acc = rbf(acc + rbf(kp[2][c] * w[c][1]));
                acc = rbf(acc + rbf(kc * w[c][0]));
                const uint32_t kv = (uint32_t)__bfloat16_as_ushort(__float2bfloat16_rn(acc * vc));
                if (tt & 1) u[c][tt >> 1] |= kv << 16; else u[c][tt >> 1] = kv;
                kp[0][c] = kp[1][c]; kp[1][c] = kp[2][c]; kp[2][c] = kc;
            }
        }
        const int jcol = t0 >> 6, ch = (t0 >> 3) & 7;
#pragma unroll
        for (int c = 0; c < 8; c++) sts128(U0 + c * CB_U_BYTES + (8 + jcol) * 128 + ((ch ^ (jcol & 7)) << 4), make_uint4(u[c][0], u[c][1], u[c][2], u[c][3]));
    }
    {
        const __nv_bfloat16* kr = ssk + (size_t)(c0 + warp) * S_;
        const uint32_t kb = K0 + warp * CB_K_BYTES;
        for (int m = lane * 2; m < 2128; m += 64) {
            const int x0 = 2048 - m, x1 = x0 - 1, x2 = x0 - 2;
            const uint32_t a0 = (x0 >= 0 && x0 < 2048) ? __bfloat16_as_ushort(kr[x0]) : 0u;
            const uint32_t a1 = (x1 >= 0 && x1 < 2048) ? __bfloat16_as_ushort(kr[x1]) : 0u;
            const uint32_t a2 = (x2 >= 0 && x2 < 2048) ? __bfloat16_as_ushort(kr[x2]) : 0u;
            sts32(kb + m * 2, a0 | (a1 << 16));
            sts32(kb + CB_K_COPY + 64 + m * 2, a1 | (a2 << 16));
        }
    }
    __syncthreads();
    const int g = lane >> 2, t = lane & 3, li = lane >> 3, lr = lane & 7;
    float acc[4][4][4];
#pragma unroll
    for (int a = 0; a < 4; a++)
#pragma unroll
        for (int b = 0; b < 4; b++) { acc[a][b][0] = acc[a][b][1] = acc[a][b][2] = acc[a][b][3] = 0.f; }
    const uint32_t kw0 = K0 + warp * CB_K_BYTES + ((g & 1) ? CB_K_COPY + 64 : 0) + (uint32_t)(2048 - g + 2 * t - (g & 1)) * 2;
    const uint32_t ub = U0 + warp * CB_U_BYTES;
#pragma unroll 1
    for (int l = 0; l < 32; l++) {
        uint32_t wv[15];
#pragma unroll
        for (int e = 0; e < 15; e++) { asm volatile("ld.shared.u32 %0,[%1];" : "=r"(wv[e]) : "r"(kw0 - (uint32_t)(64 * l + 8 * (e - 7)) * 2)); }
        const int q0 = l >> 3;
#pragma unroll
        for (int ni = 0; ni < 4; ni++) {
            if (ni >= q0) {
                const int jc = 8 + 8 * ni + lr - l;
#pragma unroll
                for (int kp = 0; kp < 2; kp++) {
                    uint32_t b[4];
                    ldsm4(b, ub + jc * 128 + (((4 * kp + li) ^ (jc & 7)) << 4));
#pragma unroll
                    for (int kq = 0; kq < 2; kq++) {
                        const int kk = 2 * kp + kq;
#pragma unroll
                        for (int mi = 0; mi < 4; mi++) {
                            const int e = 7 + 2 * (mi - kk);
                            mma16816(acc[mi][ni], wv[e], wv[e + 1], wv[e - 1], wv[e], b[2 * kq], b[2 * kq + 1]);
                        }
                    }
                }
            }
        }
    }
    __syncthreads();
    const uint32_t Y0 = K0;
#pragma unroll
    for (int mi = 0; mi < 4; mi++)
#pragma unroll
        for (int ni = 0; ni < 4; ni++)
#pragma unroll
            for (int e = 0; e < 4; e++) {
                const int r = 16 * mi + g + (e >> 1) * 8, i = 8 * ni + 2 * t + (e & 1);
                const unsigned short hv = __bfloat16_as_ushort(__float2bfloat16_rn(acc[mi][ni][e]));
                asm volatile("st.shared.u16 [%0],%1;" ::"r"(Y0 + (64 * i + r) * 16 + warp * 2), "h"(hv) : "memory");
            }
    __syncthreads();
    float Dv[8];
    { const uint4 x = ldg_nc128(ssD + c0); const uint32_t xx[4] = {x.x, x.y, x.z, x.w};
#pragma unroll
      for (int c = 0; c < 8; c++) Dv[c] = bf2f((xx[c >> 1] >> ((c & 1) * 16)) & 0xffff); }
    for (int tt = tid; tt < S_; tt += 256) {
        const uint4 y = lds128(Y0 + tt * 16), qq = ldg_nc128(q + (size_t)tt * DM + c0);
        const uint32_t yy[4] = {y.x, y.y, y.z, y.w}, qx[4] = {qq.x, qq.y, qq.z, qq.w};
        const int jc = 8 + (tt >> 6), cc = tt & 63;
        uint32_t o[4];
#pragma unroll
        for (int c = 0; c < 8; c++) {
            unsigned short kvh;
            asm volatile("ld.shared.u16 %0,[%1];" : "=h"(kvh) : "r"(U0 + c * CB_U_BYTES + jc * 128 + (((cc >> 3) ^ (jc & 7)) << 4) + (cc & 7) * 2));
            const float kv = bf2f(kvh), yv = bf2f((yy[c >> 1] >> ((c & 1) * 16)) & 0xffff), qv = bf2f((qx[c >> 1] >> ((c & 1) * 16)) & 0xffff);
            const float y2 = rbf(yv + rbf(kv * Dv[c]));
            const uint32_t r = (uint32_t)__bfloat16_as_ushort(__float2bfloat16_rn(qv * y2));
            if (c & 1) o[c >> 1] |= r << 16; else o[c >> 1] = r;
        }
        *(uint4*)(out + (size_t)tt * 1280 + 640 + c0) = make_uint4(o[0], o[1], o[2], o[3]);
    }
}

typedef CUresult (*PFN_encodeTiled)(CUtensorMap*, CUtensorMapDataType, cuuint32_t, void*, const cuuint64_t*, const cuuint64_t*,
                                    const cuuint32_t*, const cuuint32_t*, CUtensorMapInterleave, CUtensorMapSwizzle,
                                    CUtensorMapL2promotion, CUtensorMapFloatOOBfill);
static PFN_encodeTiled get_encode() {
    static PFN_encodeTiled fn = nullptr;
    if (!fn) {
        void* p = nullptr; cudaDriverEntryPointQueryResult st;
        cudaGetDriverEntryPoint("cuTensorMapEncodeTiled", &p, cudaEnableDefault, &st);
        fn = (PFN_encodeTiled)p;
    }
    return fn;
}
static void make_map(CUtensorMap* m, const void* base, uint64_t cols, uint64_t rows, uint64_t row_stride_bytes, uint32_t box_c, uint32_t box_r,
                     CUtensorMapSwizzle swz = CU_TENSOR_MAP_SWIZZLE_128B) {
    cuuint64_t dims[2] = {cols, rows}; cuuint64_t strides[1] = {row_stride_bytes};
    cuuint32_t box[2] = {box_c, box_r}; cuuint32_t es[2] = {1, 1};
    get_encode()(m, CU_TENSOR_MAP_DATA_TYPE_BFLOAT16, 2, (void*)base, dims, strides, box, es, CU_TENSOR_MAP_INTERLEAVE_NONE, swz,
                 CU_TENSOR_MAP_L2_PROMOTION_L2_128B, CU_TENSOR_MAP_FLOAT_OOB_FILL_NONE);
}

extern "C" void kernel_launch(void* const* d_in, const int* in_sizes, int n_in, void* d_out, int out_size) {
    const __nv_bfloat16* x = (const __nv_bfloat16*)d_in[0];
    const __nv_bfloat16* mem0 = (const __nv_bfloat16*)d_in[1];
    const __nv_bfloat16* Wq = (const __nv_bfloat16*)d_in[2];
    const __nv_bfloat16* Wk = (const __nv_bfloat16*)d_in[3];
    const __nv_bfloat16* Wv = (const __nv_bfloat16*)d_in[4];
    const __nv_bfloat16* Wo = (const __nv_bfloat16*)d_in[5];
    CUtensorMap tmX, tmWq, tmWk, tmWv;
    make_map(&tmX, x, DM, S_, DM * 2, 64, 32);
    make_map(&tmWq, Wq, 4096, DM, 8192, 64, 128);
    make_map(&tmWk, Wk, 4096, DM, 8192, 64, 128);
    make_map(&tmWv, Wv, 4096, DM, 8192, 64, 128);
    cudaFuncSetAttribute(k1_chain, cudaFuncAttributeMaxDynamicSharedMemorySize, K1_SMEM);
    cudaStream_t st = cudaStreamPerThread;
    cudaLaunchConfig_t cfg = {};
    cfg.gridDim = dim3(K1_CTAS); cfg.blockDim = dim3(K1_THREADS); cfg.dynamicSmemBytes = K1_SMEM; cfg.stream = st;
    cudaLaunchAttribute at[1];
    at[0].id = cudaLaunchAttributeClusterDimension; at[0].val.clusterDim.x = 3; at[0].val.clusterDim.y = 1; at[0].val.clusterDim.z = 1;
    cfg.attrs = at; cfg.numAttrs = 1;
    K1Params prm{mem0, Wo};
    cudaLaunchKernelEx(&cfg, k1_chain, tmX, tmWq, tmWk, tmWv, prm);
    void* oxp; cudaGetSymbolAddress(&oxp, g_ox);
    CUtensorMap tmO, tmWo;
    make_map(&tmO, oxp, 4096, S_, 8192, 64, 128);
    make_map(&tmWo, Wo, DM, 4096, DM * 2, 64, 64);
    cudaFuncSetAttribute(k2a_attn, cudaFuncAttributeMaxDynamicSharedMemorySize, K2A_SMEM);
    cudaFuncSetAttribute(k2b_outproj, cudaFuncAttributeMaxDynamicSharedMemorySize, K2B_SMEM);
    cudaFuncSetAttribute(k2c_conv, cudaFuncAttributeMaxDynamicSharedMemorySize, K2C_SMEM);
    k2a_attn<<<512, 256, K2A_SMEM, st>>>();
    k2b_outproj<<<80, 384, K2B_SMEM, st>>>(tmO, tmWo, (__nv_bfloat16*)d_out);
    k2c_conv<<<80, 256, K2C_SMEM, st>>>((const __nv_bfloat16*)d_in[7], (const __nv_bfloat16*)d_in[8], (const __nv_bfloat16*)d_in[9],
        (const __nv_bfloat16*)d_in[10], (const __nv_bfloat16*)d_in[11], (const __nv_bfloat16*)d_in[12], (__nv_bfloat16*)d_out);
}
```

```cpp
#include <cuda_runtime.h>
#include <cuda_bf16.h>
#include <cuda.h>
#include <stdint.h>
#include <type_traits>

#define D1 350
#define D2 170
#define NPROBE 4
#define QPD 4
#define DNR 520
#define TSPLIT 13
#define GSPLIT 34
#define NPRE 6
#define L12 1
#define L13 2
#define L14 3
#define SHARED_FIN 12
#define NA_RES 10
#define ASTAG 0
#define DSLEEP 300
#define ABLOCK 1
#define L16 3
#define L17 3
#define NST 4
#define PDL 1
#define WPROMO CU_TENSOR_MAP_L2_PROMOTION_L2_256B
#define DEVI __device__ __forceinline__
constexpr int SPIN_LIMIT = 1 << 22;

DEVI uint32_t smem_u32(const void* p) { return (uint32_t)__cvta_generic_to_shared(p); }
DEVI uint32_t mapa(uint32_t a, uint32_t rank) { uint32_t o; asm("mapa.shared::cluster.u32 %0,%1,%2;" : "=r"(o) : "r"(a), "r"(rank)); return o; }
DEVI void mbar_init(uint32_t b, uint32_t c) { asm volatile("mbarrier.init.shared::cta.b64 [%0],%1;" ::"r"(b), "r"(c) : "memory"); }
DEVI void mbar_expect(uint32_t b, uint32_t bytes) { asm volatile("mbarrier.arrive.expect_tx.shared::cta.b64 _,[%0],%1;" ::"r"(b), "r"(bytes) : "memory"); }
DEVI void mbar_arrive(uint32_t b) { asm volatile("mbarrier.arrive.shared::cta.b64 _,[%0];" ::"r"(b) : "memory"); }
DEVI bool mbar_try(uint32_t b, uint32_t ph) {
    uint32_t ok;
    asm volatile("{.reg .pred p; mbarrier.try_wait.parity.shared::cta.b64 p,[%1],%2; selp.u32 %0,1,0,p;}" : "=r"(ok) : "r"(b), "r"(ph) : "memory");
    return ok;
}
DEVI bool mbar_try_cl(uint32_t b, uint32_t ph) {
    uint32_t ok;
    asm volatile("{.reg .pred p; mbarrier.try_wait.parity.acquire.cluster.shared::cta.b64 p,[%1],%2; selp.u32 %0,1,0,p;}" : "=r"(ok) : "r"(b), "r"(ph) : "memory");
    return ok;
}
DEVI void mbar_wait(uint32_t b, uint32_t ph) { int g = 0; while (!mbar_try(b, ph)) { if (++g > SPIN_LIMIT) __trap(); } }
DEVI void mbar_wait_cl(uint32_t b, uint32_t ph) { int g = 0; while (!mbar_try_cl(b, ph)) { if (++g > SPIN_LIMIT) __trap(); } }
DEVI void bar_sync(int id, int n) { asm volatile("bar.sync %0,%1;" ::"r"(id), "r"(n) : "memory"); }
DEVI void bar_arrive(int id, int n) { asm volatile("bar.arrive %0,%1;" ::"r"(id), "r"(n) : "memory"); }
DEVI void cluster_arrive() { asm volatile("barrier.cluster.arrive.aligned;" ::: "memory"); }
DEVI void cluster_arrive_relaxed() { asm volatile("barrier.cluster.arrive.relaxed.aligned;" ::: "memory"); }
DEVI void cluster_wait() { asm volatile("barrier.cluster.wait.aligned;" ::: "memory"); }
DEVI void fence_async_smem() { asm volatile("fence.proxy.async.shared::cta;" ::: "memory"); }
DEVI bool elect_one() {
    uint32_t p;
    asm volatile("{.reg .pred P; elect.sync _|P, 0xffffffff; selp.u32 %0,1,0,P;}" : "=r"(p));
    return p;
}
DEVI void ldsm4(uint32_t* r, uint32_t a) { asm volatile("ldmatrix.sync.aligned.m8n8.x4.shared.b16 {%0,%1,%2,%3},[%4];" : "=r"(r[0]), "=r"(r[1]), "=r"(r[2]), "=r"(r[3]) : "r"(a) : "memory"); }
DEVI void ldsm4t(uint32_t* r, uint32_t a) { asm volatile("ldmatrix.sync.aligned.m8n8.x4.trans.shared.b16 {%0,%1,%2,%3},[%4];" : "=r"(r[0]), "=r"(r[1]), "=r"(r[2]), "=r"(r[3]) : "r"(a) : "memory"); }
DEVI void ldsm2t(uint32_t* r, uint32_t a) { asm volatile("ldmatrix.sync.aligned.m8n8.x2.trans.shared.b16 {%0,%1},[%2];" : "=r"(r[0]), "=r"(r[1]) : "r"(a) : "memory"); }
DEVI void stsm4(uint32_t a, uint32_t r0, uint32_t r1, uint32_t r2, uint32_t r3) { asm volatile("stmatrix.sync.aligned.m8n8.x4.shared.b16 [%0],{%1,%2,%3,%4};" ::"r"(a), "r"(r0), "r"(r1), "r"(r2), "r"(r3) : "memory"); }
DEVI void stsm4t(uint32_t a, uint32_t r0, uint32_t r1, uint32_t r2, uint32_t r3) { asm volatile("stmatrix.sync.aligned.m8n8.x4.trans.shared.b16 [%0],{%1,%2,%3,%4};" ::"r"(a), "r"(r0), "r"(r1), "r"(r2), "r"(r3) : "memory"); }
DEVI void stsm2t(uint32_t a, uint32_t r0, uint32_t r1) { asm volatile("stmatrix.sync.aligned.m8n8.x2.trans.shared.b16 [%0],{%1,%2};" ::"r"(a), "r"(r0), "r"(r1) : "memory"); }
DEVI void mma16816(float* d, uint32_t a0, uint32_t a1, uint32_t a2, uint32_t a3, uint32_t b0, uint32_t b1) {
    asm volatile("mma.sync.aligned.m16n8k16.row.col.f32.bf16.bf16.f32 {%0,%1,%2,%3},{%4,%5,%6,%7},{%8,%9},{%0,%1,%2,%3};"
                 : "+f"(d[0]), "+f"(d[1]), "+f"(d[2]), "+f"(d[3]) : "r"(a0), "r"(a1), "r"(a2), "r"(a3), "r"(b0), "r"(b1));
}
DEVI uint32_t pack_bf16(float lo, float hi) { uint32_t r; asm("cvt.rn.bf16x2.f32 %0,%1,%2;" : "=r"(r) : "f"(hi), "f"(lo)); return r; }
DEVI uint4 lds128(uint32_t a) { uint4 v; asm volatile("ld.shared.v4.u32 {%0,%1,%2,%3},[%4];" : "=r"(v.x), "=r"(v.y), "=r"(v.z), "=r"(v.w) : "r"(a) : "memory"); return v; }
DEVI float2 lds64f(uint32_t a) { float2 v; asm volatile("ld.shared.v2.f32 {%0,%1},[%2];" : "=f"(v.x), "=f"(v.y) : "r"(a) : "memory"); return v; }
DEVI float4 lds128f(uint32_t a) { float4 v; asm volatile("ld.shared.v4.f32 {%0,%1,%2,%3},[%4];" : "=f"(v.x), "=f"(v.y), "=f"(v.z), "=f"(v.w) : "r"(a) : "memory"); return v; }
DEVI void sts128(uint32_t a, uint4 v) { asm volatile("st.shared.v4.u32 [%0],{%1,%2,%3,%4};" ::"r"(a), "r"(v.x), "r"(v.y), "r"(v.z), "r"(v.w) : "memory"); }
DEVI void sts32(uint32_t a, uint32_t v) { asm volatile("st.shared.u32 [%0],%1;" ::"r"(a), "r"(v) : "memory"); }
DEVI void st_async64f(uint32_t a, float x, float y, uint32_t bar) { asm volatile("st.async.weak.shared::cluster.mbarrier::complete_tx::bytes.v2.f32 [%0],{%1,%2},[%3];" ::"r"(a), "f"(x), "f"(y), "r"(bar) : "memory"); }
DEVI void st_async128f(uint32_t a, float x, float y, float z, float w, uint32_t bar) { asm volatile("st.async.weak.shared::cluster.mbarrier::complete_tx::bytes.v4.f32 [%0],{%1,%2,%3,%4},[%5];" ::"r"(a), "f"(x), "f"(y), "f"(z), "f"(w), "r"(bar) : "memory"); }
DEVI void st_async128(uint32_t a, uint4 v, uint32_t bar) { asm volatile("st.async.weak.shared::cluster.mbarrier::complete_tx::bytes.v4.b32 [%0],{%1,%2,%3,%4},[%5];" ::"r"(a), "r"(v.x), "r"(v.y), "r"(v.z), "r"(v.w), "r"(bar) : "memory"); }
DEVI uint4 ldg_relaxed128(const void* p) { uint4 v; asm volatile("ld.relaxed.gpu.global.v4.u32 {%0,%1,%2,%3},[%4];" : "=r"(v.x), "=r"(v.y), "=r"(v.z), "=r"(v.w) : "l"(p) : "memory"); return v; }
DEVI uint32_t ldg_relaxed32(const void* p) { uint32_t v; asm volatile("ld.relaxed.gpu.global.u32 %0,[%1];" : "=r"(v) : "l"(p) : "memory"); return v; }
DEVI void stg_relaxed32(void* p, uint32_t v) { asm volatile("st.relaxed.gpu.global.u32 [%0],%1;" ::"l"(p), "r"(v) : "memory"); }
DEVI void stg_relaxed64(void* p, uint32_t a, uint32_t b) { asm volatile("st.relaxed.gpu.global.v2.u32 [%0],{%1,%2};" ::"l"(p), "r"(a), "r"(b) : "memory"); }
DEVI void stg_relaxed128(void* p, uint32_t a, uint32_t b, uint32_t c, uint32_t d) { asm volatile("st.relaxed.gpu.global.v4.u32 [%0],{%1,%2,%3,%4};" ::"l"(p), "r"(a), "r"(b), "r"(c), "r"(d) : "memory"); }
DEVI uint4 ldg_nc128(const void* p) { uint4 v; asm volatile("ld.global.nc.L1::no_allocate.v4.u32 {%0,%1,%2,%3},[%4];" : "=r"(v.x), "=r"(v.y), "=r"(v.z), "=r"(v.w) : "l"(p)); return v; }
DEVI void tma2d(uint32_t dst, const CUtensorMap* tm, int c0, int c1, uint32_t bar) {
    asm volatile("cp.async.bulk.tensor.2d.shared::cluster.global.mbarrier::complete_tx::bytes [%0],[%1,{%2,%3}],[%4];" ::"r"(dst), "l"(tm), "r"(c0), "r"(c1), "r"(bar) : "memory");
}
DEVI void tma2d_mc(uint32_t dst, const CUtensorMap* tm, int c0, int c1, uint32_t bar, uint16_t mask) {
    asm volatile("cp.async.bulk.tensor.2d.shared::cluster.global.mbarrier::complete_tx::bytes.multicast::cluster [%0],[%1,{%2,%3}],[%4],%5;" ::"r"(dst), "l"(tm), "r"(c0), "r"(c1), "r"(bar), "h"(mask) : "memory");
}
DEVI void bulk_s2s(uint32_t dst, uint32_t src, uint32_t bytes, uint32_t bar) {
    asm volatile("cp.async.bulk.shared::cluster.shared::cta.mbarrier::complete_tx::bytes [%0],[%1],%2,[%3];" ::"r"(dst), "r"(src), "r"(bytes), "r"(bar) : "memory");
}
DEVI void bulk_s2g(void* dst, uint32_t src, uint32_t bytes) {
    asm volatile("cp.async.bulk.global.shared::cta.bulk_group [%0],[%1],%2;" ::"l"(dst), "r"(src), "r"(bytes) : "memory");
}
DEVI void bulk_commit() { asm volatile("cp.async.bulk.commit_group;" ::: "memory"); }
DEVI void bulk_wait_read0() { asm volatile("cp.async.bulk.wait_group.read 0;" ::: "memory"); }
DEVI void bulk_wait_read1() { asm volatile("cp.async.bulk.wait_group.read 1;" ::: "memory"); }
DEVI void bulk_wait0() { asm volatile("cp.async.bulk.wait_group 0;" ::: "memory"); }
DEVI void wg_fence() { asm volatile("wgmma.fence.sync.aligned;" ::: "memory"); }
DEVI void wg_commit() { asm volatile("wgmma.commit_group.sync.aligned;" ::: "memory"); }
template <int N> DEVI void wg_wait() { asm volatile("wgmma.wait_group.sync.aligned %0;" ::"n"(N) : "memory"); }
template <int ACC> DEVI void wgmma_rs_n32(float* d, const uint32_t* a, uint64_t desc) {
    asm volatile("wgmma.mma_async.sync.aligned.m64n32k16.f32.bf16.bf16 {%0,%1,%2,%3,%4,%5,%6,%7,%8,%9,%10,%11,%12,%13,%14,%15},{%16,%17,%18,%19},%20,%21,1,1,0;"
                 : "+f"(d[0]), "+f"(d[1]), "+f"(d[2]), "+f"(d[3]), "+f"(d[4]), "+f"(d[5]), "+f"(d[6]), "+f"(d[7]), "+f"(d[8]), "+f"(d[9]), "+f"(d[10]), "+f"(d[11]), "+f"(d[12]), "+f"(d[13]), "+f"(d[14]), "+f"(d[15])
                 : "r"(a[0]), "r"(a[1]), "r"(a[2]), "r"(a[3]), "l"(desc), "n"(ACC));
}
DEVI float ex2(float x) { float y; asm("ex2.approx.ftz.f32 %0,%1;" : "=f"(y) : "f"(x)); return y; }

DEVI void mma16816_h(float* d, uint32_t a0, uint32_t a2, uint32_t b0, uint32_t b1) {
    asm volatile("mma.sync.aligned.m16n8k16.row.col.f32.bf16.bf16.f32 {%0,%1,%2,%3},{%4,%4,%5,%5},{%6,%7},{%0,%1,%2,%3};"
                 : "+f"(d[0]), "+f"(d[1]), "+f"(d[2]), "+f"(d[3]) : "r"(a0), "r"(a2), "r"(b0), "r"(b1));
}
DEVI void mma1688(float* d, uint32_t a0, uint32_t a1, uint32_t b0) {
    asm volatile("mma.sync.aligned.m16n8k8.row.col.f32.bf16.bf16.f32 {%0,%1,%2,%3},{%4,%5},{%6},{%0,%1,%2,%3};"
                 : "+f"(d[0]), "+f"(d[1]), "+f"(d[2]), "+f"(d[3]) : "r"(a0), "r"(a1), "r"(b0));
}
DEVI void mma1688_h(float* d, uint32_t a0, uint32_t b0) {
    asm volatile("mma.sync.aligned.m16n8k8.row.col.f32.bf16.bf16.f32 {%0,%1,%2,%3},{%4,%4},{%5},{%0,%1,%2,%3};"
                 : "+f"(d[0]), "+f"(d[1]), "+f"(d[2]), "+f"(d[3]) : "r"(a0), "r"(b0));
}

constexpr int S_ = 2048, DM = 640, NH = 32, DH = 128, NSEG = 64;
constexpr int K1_THREADS = 384, K1_CTAS = 96;
constexpr uint32_t OFF_WO = 0, OFF_X = 65536, OFF_MEMS = 147456, OFF_V = 157696, OFF_QX = 178176, OFF_KX = 186368,
                   OFF_QM = 196608, OFF_S = 197632, OFF_OS = 202752, OFF_TSA = 204800, OFF_TSC = 209920, OFF_OST = 220160, OFF_BAR = 229376;
constexpr uint32_t K1_SMEM = OFF_BAR + 256 + 1024;
constexpr uint32_t XBYTES = 40960, VBYTES = 10240, KXBYTES = 5120;
enum { BAR_W = 0, BAR_X0 = 8, BAR_S0 = 24, BAR_VX0 = 40, BAR_XF0 = 56, BAR_WO = 72, BAR_TS = 80 };
enum { NB_MAIN = 1, NB_MEM = 2, NB_PART = 3, NB_QK = 4, NB_O = 5, NB_HELP = 6, NB_EPI = 7, NB_G2 = 8, NB_SC = 9 };

__device__ unsigned char g_scr_raw[4u << 20];
__device__ unsigned g_bar1;
__device__ int g_side[K1_CTAS];
__device__ __nv_bfloat16 g_ox[(size_t)S_ * 4096];
constexpr uint32_t QKV_IMG = 8192 + 2 * 5120 + 10240;
__device__ __align__(128) unsigned char g_qkv[(size_t)NSEG * NH * QKV_IMG];

DEVI int addr_par(const void* p) { return __popcll((unsigned long long)p & 0xB3000ull) & 1; }
DEVI uint32_t side_off(const char* scr, uint32_t ro, int sg, int k) { const int p = addr_par(scr + ro); return ro + (((p == sg) ? (k ? 3 : 0) : (k ? 2 : 1)) << 12); }

DEVI uint32_t tag_and(const uint4& v, uint32_t flip) { return ((v.x ^ flip) & (v.y ^ flip)) & ((v.z ^ flip) & (v.w ^ flip)); }
DEVI void keep_live(const uint4& v) { asm volatile("" ::"r"(v.x), "r"(v.y), "r"(v.z), "r"(v.w) : "memory"); }
DEVI bool sent_ok(const uint4& v) { return (v.x != ~0u) & (v.y != ~0u) & (v.z != ~0u) & (v.w != ~0u); }

DEVI int timed_atomic(void* p) {
    uint32_t v; int c0, c1;
    asm volatile("mov.u32 %0, %%clock;" : "=r"(c0)::"memory");
    asm volatile("atom.relaxed.gpu.global.add.u32 %0,[%1],1;" : "=r"(v) : "l"(p) : "memory");
    asm volatile("{.reg .pred q; setp.eq.u32 q,%1,0xffffffff; mov.u32 %0,0x7fffffff; @!q mov.u32 %0,%%clock;}" : "=r"(c1) : "r"(v) : "memory");
    return c1 - c0;
}
struct K2Ctl { unsigned qa, qg, qb, role, done, seg[64], ox[18], cnt[30]; };
__device__ K2Ctl g_ctl;
DEVI void signal_seg(int sg) { asm volatile("red.release.gpu.global.add.u32 [%0],1;" ::"l"(&g_ctl.seg[sg]) : "memory"); }
struct K1Params {
    const __nv_bfloat16* mem0;
    const __nv_bfloat16* Wo;
    const __nv_bfloat16 *Wq, *Wk, *Wv;
};

__global__ void __launch_bounds__(K1_THREADS, 1)
k1_chain(const __grid_constant__ CUtensorMap tmX, const __grid_constant__ CUtensorMap tmWq,
         const __grid_constant__ CUtensorMap tmWk, const __grid_constant__ CUtensorMap tmWv,
         const __grid_constant__ CUtensorMap tmWo, K1Params prm)
{
    extern __shared__ unsigned char smem_raw[];
    asm volatile("griddepcontrol.launch_dependents;");
    {
        const uint32_t sb0 = (smem_u32(smem_raw) + 1023u) & ~1023u, bars0 = sb0 + OFF_BAR;
        if (threadIdx.x == 256) {
            mbar_init(bars0 + BAR_W, 1); mbar_init(bars0 + BAR_WO, 1); mbar_init(bars0 + BAR_TS, 1);
            for (int i = 0; i < 2; i++) { mbar_init(bars0 + BAR_X0 + 8 * i, 1); mbar_init(bars0 + BAR_S0 + 8 * i, 1); mbar_init(bars0 + BAR_VX0 + 8 * i, 1); mbar_init(bars0 + BAR_XF0 + 8 * i, 3); }
            sts32(bars0 + 248, 0u);
            asm volatile("fence.mbarrier_init.release.cluster;" ::: "memory");
            fence_async_smem();
        }
        __syncthreads();
    }

    if (threadIdx.x < 256) {
        asm volatile("setmaxnreg.inc.sync.aligned.u32 216;");
        const int lane = __shfl_sync(~0u, (int)(threadIdx.x & 31), (int)(threadIdx.x & 31));
        const int warp = __shfl_sync(~0u, (int)(threadIdx.x >> 5), 0);
        const int tid = warp * 32 + lane;
        const int g = lane >> 2, t = lane & 3;
        const uint32_t sb = (smem_u32(smem_raw) + 1023u) & ~1023u, bars = sb + OFF_BAR;
        const int cta = blockIdx.x, h = cta / 3;
        uint32_t j; asm volatile("mov.u32 %0, %%cluster_ctarank;" : "=r"(j));
        char* const SCR = (char*)(((unsigned long long)g_scr_raw + 0x1FFFFFull) & ~0x1FFFFFull);
        const int t_begin = TSPLIT * j, t_cnt = (j == 2) ? 40 - 2 * TSPLIT : TSPLIT;
        const int wg = warp >> 2, w = warp & 3;
        const int li = lane >> 3, lr = lane & 7;
        uint32_t a[160];
        mbar_wait(bars + BAR_W, 0);
        {
            const uint32_t base = sb + OFF_X + wg * 81920 + ((li >> 1) * 8 + lr) * 128 + (((2 * w + (li & 1)) ^ lr) << 4);
#pragma unroll
            for (int kk = 0; kk < 40; kk++) ldsm4t(&a[4 * kk], base + kk * 2048);
        }
        if ((a[159] ^ a[155] ^ a[79]) == 0x7fc1a5a5u && a[158] == 0x7fc1a5a6u) __nanosleep(1);
        cluster_arrive_relaxed(); cluster_wait();

        const bool has1 = (warp + 8 < t_cnt);
        uint32_t pp0, pp1;
        {
            const int T0 = t_begin + warp, T1 = t_begin + (has1 ? warp + 8 : warp);
            const uint32_t in = (h & 15) * 256 + (t * 4 + (g >> 1)) * 16 + (g & 1) * 8;
            pp0 = side_off(SCR, T0 * 16384, 0, h >> 4) + in;
            pp1 = side_off(SCR, T1 * 16384, 0, h >> 4) + in;
        }
        const uint32_t wo_a = sb + OFF_WO + (warp >> 2) * 16384 + ((li >> 1) * 8 + lr) * 128 + (((2 * w + (li & 1)) ^ lr) << 4);
        const uint64_t descX0 = (uint64_t)(((sb + OFF_X) & 0x3FFFF) >> 4) | (1ull << 16) | (64ull << 32) | (1ull << 62);
        const uint32_t l16 = sb + lane * 16;
        const uint32_t swz = ((2 * w + (li & 1)) ^ lr) << 4;
        const uint32_t st_m = (j < 2) ? sb + (wg ? OFF_KX + 32 * 128 : OFF_QM) + lr * 128 + swz
                                      : sb + OFF_V + (32 + lr) * 256 + wg * 128 + swz;
        const uint32_t st_m_par = (j < 2) ? (wg ? KXBYTES : 0) : VBYTES;
        const uint32_t st_x = (j < 2) ? sb + (wg ? OFF_KX : OFF_QX) + ((li >> 1) * 8 + lr) * 128 + swz
                                      : sb + OFF_V + ((li >> 1) * 8 + lr) * 256 + wg * 128 + swz;
        const uint32_t st_x_par = (j < 2) ? (wg ? KXBYTES : 4096) : VBYTES;
        const uint32_t st_x_q = (j < 2) ? 16 * 128 : 16 * 256;

        auto token_gemm = [&](int sg) {
            const int p = sg & 1;
            mbar_wait(bars + BAR_X0 + 8 * p, (sg >> 1) & 1);
            float d[16];
#pragma unroll
            for (int i = 0; i < 16; i++) d[i] = 0.f;
            const uint64_t dx = descX0 + (uint64_t)(p * (XBYTES >> 4));
            wg_fence();
            wgmma_rs_n32<0>(d, &a[0], dx);
#pragma unroll
            for (int kk = 1; kk < GSPLIT; kk++) wgmma_rs_n32<1>(d, &a[4 * kk], dx + (uint64_t)((kk >> 2) * 256 + (kk & 3) * 2));
            wg_commit();
            if (sg > 0) bar_sync(NB_G2, 384);
#pragma unroll
            for (int kk = GSPLIT; kk < 40; kk++) wgmma_rs_n32<1>(d, &a[4 * kk], dx + (uint64_t)((kk >> 2) * 256 + (kk & 3) * 2));
            wg_commit();
            wg_wait<0>();
#pragma unroll
            for (int q = 0; q < 2; q++)
                stsm4t(st_x + p * st_x_par + q * st_x_q, pack_bf16(d[8 * q + 0], d[8 * q + 1]), pack_bf16(d[8 * q + 2], d[8 * q + 3]),
                       pack_bf16(d[8 * q + 4], d[8 * q + 5]), pack_bf16(d[8 * q + 6], d[8 * q + 7]));
            fence_async_smem();
            if (sg < NSEG - 1) bar_arrive(NB_EPI, 384);
            if (j == 2 && sg < NSEG - 1) {
                bar_sync(NB_MAIN, 256);
                if (tid < 2) bulk_s2s(mapa(sb + OFF_V + p * VBYTES, tid), sb + OFF_V + p * VBYTES, 8192, mapa(bars + BAR_VX0 + 8 * p, tid));
            }
        };
        auto store_image = [&](int sg) {
            const int p = sg & 1;
            unsigned char* dst = g_qkv + (size_t)(sg * NH + h) * QKV_IMG;
            if (j < 2) {
                bulk_s2g(dst + j * 4096, sb + OFF_QX + p * 4096, 4096);
                bulk_s2g(dst + 8192 + j * KXBYTES, sb + OFF_KX + p * KXBYTES, KXBYTES);
            } else {
                bulk_s2g(dst + 8192 + 2 * KXBYTES, sb + OFF_V + p * VBYTES, VBYTES);
            }
            bulk_commit();
        };
        auto bulk_traffic = [&](int s) {
            const int p = s & 1;
#pragma unroll
            for (int r3 = 0; r3 < 3; r3++) asm volatile("mbarrier.arrive.relaxed.cluster.shared::cluster.b64 _,[%0];" ::"r"(mapa(bars + BAR_XF0 + 8 * p, r3)) : "memory");
            if (s >= 1) store_image(s - 1);
            if (s + 2 < NSEG) {
                mbar_wait(bars + BAR_XF0 + 8 * p, (s >> 1) & 1);
                mbar_expect(bars + BAR_X0 + 8 * p, XBYTES);
#pragma unroll 1
                for (int bx = j; bx < 10; bx += 3) tma2d_mc(sb + OFF_X + p * XBYTES + bx * 4096, &tmX, bx * 64, (s + 2) * 32, bars + BAR_X0 + 8 * p, (uint16_t)7);
            }
            bulk_wait_read0();
        };
        token_gemm(0);

#pragma unroll 1
        for (int s = 0; s < NSEG; s++) {
            const int p = s & 1, ph = (s >> 1) & 1;
            const bool last = (s == NSEG - 1);
            bar_sync(NB_MEM, 384);
            {
                float c0[4] = {0.f, 0.f, 0.f, 0.f}, c1[4] = {0.f, 0.f, 0.f, 0.f};
                const uint32_t mb = l16 + OFF_MEMS;
                uint32_t bq[QPD + 1][4];
#pragma unroll
                for (int i = 0; i < QPD; i++) ldsm4(bq[i], mb + i * 512);
#pragma unroll
                for (int kp = 0; kp < 20; kp++) {
                    if (kp + QPD < 20) ldsm4(bq[(kp + QPD) % (QPD + 1)], mb + (kp + QPD) * 512);
                    mma16816(c0, a[8 * kp + 0], a[8 * kp + 1], a[8 * kp + 2], a[8 * kp + 3], bq[kp % (QPD + 1)][0], bq[kp % (QPD + 1)][1]);
                    mma16816(c1, a[8 * kp + 4], a[8 * kp + 5], a[8 * kp + 6], a[8 * kp + 7], bq[kp % (QPD + 1)][2], bq[kp % (QPD + 1)][3]);
                }
                stsm2t(st_m + p * st_m_par, pack_bf16(c0[0] + c1[0], c0[1] + c1[1]), pack_bf16(c0[2] + c1[2], c0[3] + c1[3]));
            }
            if (!last) {
                if (j < 2 && warp == 0) {
                    bar_sync(NB_QK, 384);
                    uint32_t q0[4], q1[4], q2[4], q3[4], kc[4], kd[4];
                    const uint32_t qaddr = sb + OFF_QM + lr * 128 + (((li >> 1) ^ lr) << 4), km = sb + OFF_KX + p * KXBYTES + (32 + lr) * 128 + ((li ^ lr) << 4);
                    ldsm4(q0, qaddr); ldsm4(kc, km); ldsm4(q2, qaddr ^ 64); ldsm4(kd, km ^ 64); ldsm4(q1, qaddr ^ 32); ldsm4(q3, qaddr ^ 96);
                    float m0[4] = {0.f, 0.f, 0.f, 0.f}, m1[4] = {0.f, 0.f, 0.f, 0.f};
                    mma16816(m0, q0[0], q0[1], q0[2], q0[3], kc[0], kc[1]);
                    mma16816(m1, q2[0], q2[1], q2[2], q2[3], kd[0], kd[1]);
                    mma16816(m0, q1[0], q1[1], q1[2], q1[3], kc[2], kc[3]);
                    mma16816(m1, q3[0], q3[1], q3[2], q3[3], kd[2], kd[3]);
                    const uint32_t d4 = sb + OFF_S + p * 2560 + j * 1280 + 4 * 256 + lane * 8, sbar = bars + BAR_S0 + 8 * p;
#pragma unroll
                    for (int r3 = 0; r3 < 3; r3++) st_async64f(mapa(d4, r3), m0[0] + m1[0], m0[1] + m1[1], mapa(sbar, r3));
                } else {
                    bar_arrive(NB_QK, 384);
                }
                if (s == 0) mbar_wait(bars + BAR_WO, 0);
                bar_sync(NB_SC, 384);
                uint32_t wf[4 * NPRE];
#pragma unroll
                for (int kk = 0; kk < NPRE; kk++) ldsm4t(&wf[4 * kk], wo_a + kk * 2048);
                if (warp == 7) { if (lane == 0) bulk_traffic(s); __syncwarp(); }
                bar_sync(NB_O, 384);
                const uint32_t tag = ph ^ 1, so = (uint32_t)p << 20;
                float e0[4] = {0.f, 0.f, 0.f, 0.f}, e1[4] = {0.f, 0.f, 0.f, 0.f}, f0[4] = {0.f, 0.f, 0.f, 0.f}, f1[4] = {0.f, 0.f, 0.f, 0.f};
#pragma unroll
                for (int q = 0; q < 4; q++) {
                    uint32_t ob[4];
                    ldsm4(ob, l16 + OFF_OS + q * 512);
                    if (2 * q + 1 < NPRE) {
                        mma16816(e0, wf[(8 * q + 0) % (4 * NPRE)], wf[(8 * q + 1) % (4 * NPRE)], wf[(8 * q + 2) % (4 * NPRE)], wf[(8 * q + 3) % (4 * NPRE)], ob[0], ob[1]);
                        mma16816(e1, wf[(8 * q + 4) % (4 * NPRE)], wf[(8 * q + 5) % (4 * NPRE)], wf[(8 * q + 6) % (4 * NPRE)], wf[(8 * q + 7) % (4 * NPRE)], ob[2], ob[3]);
                    } else {
                        uint32_t u0[4], u1[4];
                        ldsm4t(u0, wo_a + q * 4096);
                        ldsm4t(u1, wo_a + q * 4096 + 2048);
                        mma16816(e0, u0[0], u0[1], u0[2], u0[3], ob[0], ob[1]);
                        mma16816(e1, u1[0], u1[1], u1[2], u1[3], ob[2], ob[3]);
                    }
                    if (has1) {
                        uint32_t w0[4], w1[4];
                        ldsm4t(w0, wo_a + 32768 + q * 4096);
                        ldsm4t(w1, wo_a + 32768 + q * 4096 + 2048);
                        mma16816(f0, w0[0], w0[1], w0[2], w0[3], ob[0], ob[1]);
                        mma16816(f1, w1[0], w1[1], w1[2], w1[3], ob[2], ob[3]);
                    }
                }
                stg_relaxed64(SCR + (pp0 + so), (__float_as_uint(e0[0] + e1[0]) & ~1u) | tag, (__float_as_uint(e0[1] + e1[1]) & ~1u) | tag);
                stg_relaxed64(SCR + ((pp0 ^ 0x1000u) + so), (__float_as_uint(e0[2] + e1[2]) & ~1u) | tag, (__float_as_uint(e0[3] + e1[3]) & ~1u) | tag);
                if (has1) {
                    stg_relaxed64(SCR + (pp1 + so), (__float_as_uint(f0[0] + f1[0]) & ~1u) | tag, (__float_as_uint(f0[1] + f1[1]) & ~1u) | tag);
                    stg_relaxed64(SCR + ((pp1 ^ 0x1000u) + so), (__float_as_uint(f0[2] + f1[2]) & ~1u) | tag, (__float_as_uint(f0[3] + f1[3]) & ~1u) | tag);
                }
                bar_arrive(NB_PART, 384);
                if (warp == 7 && s >= 1) { if (lane == 0) { bulk_wait0(); signal_seg(s - 1); } __syncwarp(); }
            }
            if (!last) {
                if (s == NSEG - 2) {
                    fence_async_smem();
                    bar_sync(NB_MAIN, 256);
                    if (tid == 224) store_image(NSEG - 2);
                    __syncwarp();
                }
                token_gemm(s + 1);
                if (s == NSEG - 2) { if (tid == 224) { bulk_wait0(); signal_seg(NSEG - 2); } __syncwarp(); }
            }
            else {
                stg_relaxed64(SCR + (pp0 + (1u << 20)), 0u, 0u); stg_relaxed64(SCR + ((pp0 ^ 0x1000u) + (1u << 20)), 0u, 0u);
                if (has1) { stg_relaxed64(SCR + (pp1 + (1u << 20)), 0u, 0u); stg_relaxed64(SCR + ((pp1 ^ 0x1000u) + (1u << 20)), 0u, 0u); }
                bar_sync(NB_MAIN, 256);
            }
        }
        {
            constexpr int p = (NSEG - 1) & 1;
            const int mi = warp & 1;
            if (j < 2) {
                uint32_t qa[16];
#pragma unroll
                for (int kk = 0; kk < 4; kk++)
                    ldsm4(&qa[4 * kk], sb + OFF_QX + p * 4096 + (16 * mi + (li & 1) * 8 + lr) * 128 + (((2 * kk + (li >> 1)) ^ lr) << 4));
                const uint32_t dstb = mapa(sb + OFF_TSC + j * 5120 + mi * 2560 + lane * 16, 2), br = mapa(bars + BAR_TS, 2);
                const int nrep = (warp < 2) ? 2 : 1;
                for (int rep = 0; rep < nrep; rep++) {
                    const int nj = rep ? 4 : (warp >> 1);
                    uint32_t ka[4], kb[4];
                    const uint32_t kbase = sb + OFF_KX + p * KXBYTES + (8 * nj + lr) * 128 + ((li ^ lr) << 4);
                    ldsm4(ka, kbase);
                    ldsm4(kb, kbase ^ 64);
                    float s0[4] = {0.f, 0.f, 0.f, 0.f}, s1[4] = {0.f, 0.f, 0.f, 0.f};
                    mma16816(s0, qa[0], qa[1], qa[2], qa[3], ka[0], ka[1]);
                    mma16816(s1, qa[8], qa[9], qa[10], qa[11], kb[0], kb[1]);
                    mma16816(s0, qa[4], qa[5], qa[6], qa[7], ka[2], ka[3]);
                    mma16816(s1, qa[12], qa[13], qa[14], qa[15], kb[2], kb[3]);
                    st_async128f(dstb + nj * 512, s0[0] + s1[0], s0[1] + s1[1], s0[2] + s1[2], s0[3] + s1[3], br);
                }
            } else {
                if (tid == 0) mbar_expect(bars + BAR_TS, 10240);
                mbar_wait(bars + BAR_TS, 0);
                float s0[10], s1[10];
                const float sl2 = 0.08838834764831845f * 1.4426950408889634f;
                const uint32_t ta = sb + OFF_TSC + mi * 2560 + lane * 16;
                const int i0 = 16 * mi + g, i1 = i0 + 8;
                float m0 = -1e30f, m1 = -1e30f;
#pragma unroll
                for (int nj = 0; nj < 5; nj++) {
                    const float4 x = lds128f(ta + nj * 512), y = lds128f(ta + 5120 + nj * 512);
                    const int key = 8 * nj + 2 * t;
                    s0[2 * nj] = (nj == 4 || key <= i0) ? x.x + y.x : -1e30f;
                    s0[2 * nj + 1] = (nj == 4 || key + 1 <= i0) ? x.y + y.y : -1e30f;
                    s1[2 * nj] = (nj == 4 || key <= i1) ? x.z + y.z : -1e30f;
                    s1[2 * nj + 1] = (nj == 4 || key + 1 <= i1) ? x.w + y.w : -1e30f;
                    m0 = fmaxf(m0, fmaxf(s0[2 * nj], s0[2 * nj + 1])); m1 = fmaxf(m1, fmaxf(s1[2 * nj], s1[2 * nj + 1]));
                }
                m0 = fmaxf(m0, __shfl_xor_sync(~0u, m0, 1)); m1 = fmaxf(m1, __shfl_xor_sync(~0u, m1, 1));
                m0 = fmaxf(m0, __shfl_xor_sync(~0u, m0, 2)); m1 = fmaxf(m1, __shfl_xor_sync(~0u, m1, 2));
                m0 *= sl2; m1 *= sl2;
                float u0 = 0.f, u1 = 0.f;
#pragma unroll
                for (int q = 0; q < 10; q++) { s0[q] = ex2(fmaf(s0[q], sl2, -m0)); u0 += s0[q]; s1[q] = ex2(fmaf(s1[q], sl2, -m1)); u1 += s1[q]; }
                u0 += __shfl_xor_sync(~0u, u0, 1); u1 += __shfl_xor_sync(~0u, u1, 1);
                u0 += __shfl_xor_sync(~0u, u0, 2); u1 += __shfl_xor_sync(~0u, u1, 2);
                u0 = __fdividef(1.f, u0); u1 = __fdividef(1.f, u1);
                uint32_t pa[10];
#pragma unroll
                for (int nj = 0; nj < 5; nj++) { pa[2 * nj] = pack_bf16(s0[2 * nj] * u0, s0[2 * nj + 1] * u0); pa[2 * nj + 1] = pack_bf16(s1[2 * nj] * u1, s1[2 * nj + 1] * u1); }
#pragma unroll
                for (int dg = 0; dg < 2; dg++) {
                    const int cb = 4 * (warp >> 1) + 2 * dg;
                    const int c16 = cb + (li >> 1), c16b = cb + (li & 1);
                    const uint32_t vb = sb + OFF_V + p * VBYTES + ((li & 1) * 8 + lr) * 256 + (((c16 & 8) | ((c16 ^ lr) & 7)) << 4);
                    uint32_t v0[4], v1[4], v2[2];
                    ldsm4t(v0, vb); ldsm4t(v1, vb + 16 * 256);
                    ldsm2t(v2, sb + OFF_V + p * VBYTES + (32 + lr) * 256 + (((c16b & 8) | ((c16b ^ lr) & 7)) << 4));
                    float o0[4] = {0.f, 0.f, 0.f, 0.f}, o1[4] = {0.f, 0.f, 0.f, 0.f};
                    mma16816(o0, pa[0], pa[1], pa[2], pa[3], v0[0], v0[1]);
                    mma16816(o1, pa[0], pa[1], pa[2], pa[3], v0[2], v0[3]);
                    mma16816(o0, pa[4], pa[5], pa[6], pa[7], v1[0], v1[1]);
                    mma16816(o1, pa[4], pa[5], pa[6], pa[7], v1[2], v1[3]);
                    mma1688(o0, pa[8], pa[9], v2[0]);
                    mma1688(o1, pa[8], pa[9], v2[1]);
                    stsm4(sb + OFF_OST + (16 * mi + (li & 1) * 8 + lr) * 272 + (cb + (li >> 1)) * 16,
                          pack_bf16(o0[0], o0[1]), pack_bf16(o0[2], o0[3]), pack_bf16(o1[0], o1[1]), pack_bf16(o1[2], o1[3]));
                }
                bar_sync(NB_MAIN, 256);
#pragma unroll
                for (int q = 0; q < 2; q++) {
                    const int row = q * 16 + (tid >> 4), ch = tid & 15;
                    *(uint4*)(g_ox + (size_t)((NSEG - 1) * 32 + row) * 4096 + h * 128 + ch * 8) = lds128(sb + OFF_OST + row * 272 + ch * 16);
                }
                bar_sync(NB_MAIN, 256);
                if (tid == 0) asm volatile("red.release.gpu.global.add.u32 [%0],1;" ::"l"(&g_ctl.ox[17]) : "memory");
            }
        }
        cluster_arrive(); cluster_wait();
    } else {
        asm volatile("setmaxnreg.dec.sync.aligned.u32 72;");
        const int lane = __shfl_sync(~0u, (int)(threadIdx.x & 31), (int)(threadIdx.x & 31));
        const int warp = __shfl_sync(~0u, (int)(threadIdx.x >> 5), 0);
        const int tid = warp * 32 + lane;
        const int g = lane >> 2, t = lane & 3;
        const uint32_t sb = (smem_u32(smem_raw) + 1023u) & ~1023u, bars = sb + OFF_BAR;
        const int cta = blockIdx.x, h = cta / 3;
        uint32_t j; asm volatile("mov.u32 %0, %%cluster_ctarank;" : "=r"(j));
        char* const SCR = (char*)(((unsigned long long)g_scr_raw + 0x1FFFFFull) & ~0x1FFFFFull);
        const int t_begin = TSPLIT * j, t_cnt = (j == 2) ? 40 - 2 * TSPLIT : TSPLIT;
        const int ht = tid - 256, hw = warp - 8;
        const int li = lane >> 3, lr = lane & 7;
        if (hw == 0 && elect_one()) {
            mbar_expect(bars + BAR_W, 163840);
            const CUtensorMap* m0 = (j < 2) ? &tmWq : &tmWv;
            const CUtensorMap* m1 = (j < 2) ? &tmWk : &tmWv;
            const int c0 = h * 128 + ((j < 2) ? (int)j * 64 : 0), c1 = h * 128 + ((j < 2) ? (int)j * 64 : 64);
            for (int b = 0; b < 5; b++) {
                tma2d(sb + OFF_X + b * 16384, m0, c0, b * 128, bars + BAR_W);
                tma2d(sb + OFF_X + 81920 + b * 16384, m1, c1, b * 128, bars + BAR_W);
            }
        }
        if (hw == 2 && h == 0 && elect_one()) {
            for (int sg = 0; sg < 3; sg++)
                for (int bx = j; bx < 10; bx += 3)
                    asm volatile("cp.async.bulk.prefetch.tensor.2d.L2.global.tile [%0,{%1,%2}];" ::"l"(&tmX), "r"(bx * 64), "r"(sg * 32) : "memory");
        }
        __syncwarp();
        cluster_arrive_relaxed();
        uint4 m0v[5];
#pragma unroll
        for (int i = 0; i < 5; i++) { const int ch = ht + 128 * i; m0v[i] = ldg_nc128(prm.mem0 + (ch & 7) * DM + (ch >> 3) * 8); }
        unsigned bar_target = 0;
        if (hw == 3) {
            if (cta >= 80 && cta < 88) { const int q = cta - 80, sl = q >> 1; char* r = SCR + 0xA0000 + (((sl & 1) << 15) | ((sl >> 1) << 18) | ((q & 1) << 14)); for (int i = lane; i < 1024; i += 32) stg_relaxed128(r + i * 16, ~0u, ~0u, ~0u, ~0u); }
            if (lane == 0) {
                int best0 = 1 << 30, best1 = 1 << 30;
                char* p0 = SCR + side_off(SCR, 0x1A0000, 0, 0) + (cta & 31) * 128 + (cta >> 5) * 32;
                char* p1 = SCR + side_off(SCR, 0x1A0000, 1, 0) + (cta & 31) * 128 + (cta >> 5) * 32;
                stg_relaxed128(p0, 0u, 0u, 0u, 0u); stg_relaxed128(p0 + 16, 0u, 0u, 0u, 0u);
                stg_relaxed128(p1, 0u, 0u, 0u, 0u); stg_relaxed128(p1 + 16, 0u, 0u, 0u, 0u);
                for (int r = 0; r < NPROBE; r++) {
                    best0 = min(best0, timed_atomic(p0)); best1 = min(best1, timed_atomic(p1));
                    if (r >= 1 && min(best0, best1) < 450 && abs(best0 - best1) > 120) break;
                }
                stg_relaxed32(&g_side[cta], best1 < best0 ? 1u : 0u);
            }
            __threadfence();
            __syncwarp();
            if (lane == 0) { const unsigned old = atomicAdd(&g_bar1, 1u); bar_target = (old / K1_CTAS + 1) * K1_CTAS; }
        }
        cluster_wait();
        if (hw == 0 && elect_one()) {
            for (int p = 0; p < 2; p++) {
                mbar_expect(bars + BAR_X0 + 8 * p, XBYTES);
                for (int bx = j; bx < 10; bx += 3) tma2d_mc(sb + OFF_X + p * XBYTES + bx * 4096, &tmX, bx * 64, p * 32, bars + BAR_X0 + 8 * p, (uint16_t)7);
                if (p == 0) {
                    mbar_expect(bars + BAR_WO, 4 * 16384);
                    for (int b = 0; b < 4; b++) tma2d(sb + OFF_WO + b * 16384, &tmWo, t_begin * 16 + b * 64, h * 128, bars + BAR_WO);
                }
            }
        }
        __syncwarp();
#pragma unroll
        for (int i = 0; i < 5; i++) sts128(sb + OFF_MEMS + (ht + 128 * i) * 16, m0v[i]);
        bar_arrive(NB_MEM, 384);
        uint32_t pbase_ = 0, mo0_ = 0, mi0_ = 0; bool red = false;
        const uint32_t qaddr_ = sb + OFF_QM + lr * 128 + (((li >> 1) ^ lr) << 4);
        const uint32_t kaddr_ = sb + OFF_KX + (8 * hw + lr) * 128 + ((li ^ lr) << 4);
        const int c16a = 4 * hw + (li >> 1), c16m = 4 * hw + (li & 1);
        const uint32_t vxa_ = sb + OFF_V + ((li & 1) * 8 + lr) * 256 + (((c16a & 8) | ((c16a ^ lr) & 7)) << 4);
        const uint32_t vcm_ = sb + OFF_V + (32 + lr) * 256 + (((c16m & 8) | ((c16m ^ lr) & 7)) << 4);

        const int d1 = D1, d2 = D2;
#pragma unroll 1
        for (int s = 0; s < NSEG - 1; s++) {
            const int p = s & 1, ph = (s >> 1) & 1;
            uint32_t qaddr = qaddr_, kaddr = kaddr_, vxa = vxa_, vcm = vcm_, pbase, mo0, mi0, l8 = lane * 8;
            asm volatile("" : "+r"(qaddr), "+r"(kaddr), "+r"(vxa), "+r"(vcm), "+r"(l8));
            const uint32_t sdst = sb + OFF_S + j * 1280 + l8;
            if (ht == 0) {
                mbar_expect(bars + BAR_S0 + 8 * p, j < 2 ? 4608 : 2560);
                if (j < 2) mbar_expect(bars + BAR_VX0 + 8 * p, 8192);
            }
            const uint32_t sbar = bars + BAR_S0 + 8 * p;
            bar_sync(NB_EPI, 384);
            if (j < 2) {
                uint32_t ka[4], kb[4];
                ldsm4(ka, kaddr + p * KXBYTES);
                ldsm4(kb, (kaddr + p * KXBYTES) ^ 64);
                bar_sync(NB_QK, 384);
                uint32_t q0[4], q1[4], q2[4], q3[4];
                ldsm4(q0, qaddr); ldsm4(q2, qaddr ^ 64); ldsm4(q1, qaddr ^ 32); ldsm4(q3, qaddr ^ 96);
                float s0[4] = {0.f, 0.f, 0.f, 0.f}, s1[4] = {0.f, 0.f, 0.f, 0.f};
                mma16816(s0, q0[0], q0[1], q0[2], q0[3], ka[0], ka[1]);
                mma16816(s1, q2[0], q2[1], q2[2], q2[3], kb[0], kb[1]);
                mma16816(s0, q1[0], q1[1], q1[2], q1[3], ka[2], ka[3]);
                mma16816(s1, q3[0], q3[1], q3[2], q3[3], kb[2], kb[3]);
                const uint32_t d0 = sdst + p * 2560 + hw * 256;
#pragma unroll
                for (int r3 = 0; r3 < 3; r3++) st_async64f(mapa(d0, r3), s0[0] + s1[0], s0[1] + s1[1], mapa(sbar, r3));
            } else {
                bar_sync(NB_QK, 384);
                const uint32_t src = sb + OFF_V + p * VBYTES + 32 * 256 + ht * 16;
                const uint4 v = lds128(src);
                st_async128(mapa(src, 0), v, mapa(sbar, 0));
                st_async128(mapa(src, 1), v, mapa(sbar, 1));
            }
            bar_arrive(NB_SC, 384);
            uint32_t va[4], vb[4], vc[4], vd[4];
            if (j < 2) mbar_wait(bars + BAR_VX0 + 8 * p, ph);
            {
                const uint32_t b0 = vxa + p * VBYTES, b1 = (vxa ^ 0x20) + p * VBYTES;
                ldsm4t(va, b0); ldsm4t(vb, b0 + 16 * 256);
                ldsm4t(vc, b1); ldsm4t(vd, b1 + 16 * 256);
            }
            mbar_wait(sbar, ph);
            {
                float sc[10];
                const uint32_t sa = sb + OFF_S + p * 2560 + l8;
                const float sl2 = 0.08838834764831845f * 1.4426950408889634f;
#pragma unroll
                for (int nj = 0; nj < 5; nj++) {
                    const float2 x = lds64f(sa + nj * 256), y = lds64f(sa + 1280 + nj * 256);
                    sc[2 * nj] = x.x + y.x; sc[2 * nj + 1] = x.y + y.y;
                }
                uint32_t vm0[2], vm1[2];
                ldsm2t(vm0, vcm + p * VBYTES); ldsm2t(vm1, (vcm + p * VBYTES) ^ 0x20);
                float m = fmaxf(fmaxf(fmaxf(sc[0], sc[1]), fmaxf(sc[2], sc[3])), fmaxf(fmaxf(sc[4], sc[5]), fmaxf(sc[6], sc[7])));
                m = fmaxf(m, fmaxf(sc[8], sc[9]));
                m = fmaxf(m, __shfl_xor_sync(~0u, m, 1));
                m = fmaxf(m, __shfl_xor_sync(~0u, m, 2));
                const float ms = m * sl2;
                uint32_t pp[5];
#pragma unroll
                for (int nj = 0; nj < 5; nj++) pp[nj] = pack_bf16(ex2(fmaf(sc[2 * nj], sl2, -ms)), ex2(fmaf(sc[2 * nj + 1], sl2, -ms)));
                const uint32_t one2 = 0x3F803F80u;
                float su[4] = {0.f, 0.f, 0.f, 0.f};
                mma16816_h(su, pp[0], pp[1], one2, one2);
                mma16816_h(su, pp[2], pp[3], one2, one2);
                mma1688_h(su, pp[4], one2);
                const float rsum = su[0];
                float o0[4] = {0.f, 0.f, 0.f, 0.f}, o1[4] = {0.f, 0.f, 0.f, 0.f}, o2[4] = {0.f, 0.f, 0.f, 0.f}, o3[4] = {0.f, 0.f, 0.f, 0.f};
                mma16816_h(o0, pp[0], pp[1], va[0], va[1]);
                mma16816_h(o1, pp[0], pp[1], va[2], va[3]);
                mma16816_h(o2, pp[0], pp[1], vc[0], vc[1]);
                mma16816_h(o3, pp[0], pp[1], vc[2], vc[3]);
                mma16816_h(o0, pp[2], pp[3], vb[0], vb[1]);
                mma16816_h(o1, pp[2], pp[3], vb[2], vb[3]);
                mma16816_h(o2, pp[2], pp[3], vd[0], vd[1]);
                mma16816_h(o3, pp[2], pp[3], vd[2], vd[3]);
                mma1688_h(o0, pp[4], vm0[0]);
                mma1688_h(o1, pp[4], vm0[1]);
                mma1688_h(o2, pp[4], vm1[0]);
                mma1688_h(o3, pp[4], vm1[1]);
                const float inv = __fdividef(1.f, rsum);
                const uint32_t ob = sb + OFF_OS + hw * 512 + g * 16 + t * 4;
                sts32(ob, pack_bf16(o0[0] * inv, o0[1] * inv));
                sts32(ob + 128, pack_bf16(o1[0] * inv, o1[1] * inv));
                sts32(ob + 256, pack_bf16(o2[0] * inv, o2[1] * inv));
                sts32(ob + 384, pack_bf16(o3[0] * inv, o3[1] * inv));
            }
            bar_arrive(NB_O, 384);
            if (s == 0) {
                if (ht == 96) { int gd = 0; while ((int)(ldg_relaxed32(&g_bar1) - bar_target) < 0) { if (++gd > SPIN_LIMIT) __trap(); } __threadfence(); }
                bar_sync(NB_HELP, 128);
                int side, unit;
                {
                    int n_side[2] = {0, 0}, rank = 0;
                    side = (int)ldg_relaxed32(&g_side[cta]);
                    for (int q = lane; q < K1_CTAS; q += 32) {
                        const int sq = (int)ldg_relaxed32(&g_side[q]);
                        n_side[0] += (sq == 0); n_side[1] += (sq == 1); rank += (sq == side && q < cta);
                    }
                    for (int o = 16; o; o >>= 1) { n_side[0] += __shfl_xor_sync(~0u, n_side[0], o); n_side[1] += __shfl_xor_sync(~0u, n_side[1], o); rank += __shfl_xor_sync(~0u, rank, o); }
                    const int n_other = n_side[side ^ 1];
                    if (rank < 40) unit = 2 * rank + side;
                    else unit = (n_other + (rank - 40) < 40) ? 2 * (n_other + (rank - 40)) + (side ^ 1) : -1;
                }
                red = unit >= 0;
                const int u = red ? unit : 0;
                const int rc = lane & 3, hg = lane >> 2;
                pbase_ = side_off(SCR, (u >> 1) * 16384, u & 1, hg >> 2) + ((hg * 4) & 15) * 256 + (hw * 4 + rc) * 16;
                {
                    const int chunk = u * 8 + 2 * hw + ((lane >> 4) & 1), kb = chunk >> 8, off = (chunk & 255) * 16 + rc * 4;
                    mo0_ = ((kb < 2) ? side_off(SCR, 0xA0000, 0, kb) : side_off(SCR, 0xA0000 + 16384, 0, 0)) + off;
                }
                mi0_ = side_off(SCR, 0xA0000, side, 0) + ht * 16;
            }
            pbase = pbase_; mo0 = mo0_; mi0 = mi0_;
            asm volatile("" : "+r"(pbase), "+r"(mo0), "+r"(mi0));
            bar_sync(NB_PART, 384);
            const int nsl = (s + 1) & 3, rsl = (s + 3) & 3;
            const uint32_t nso = ((nsl & 1) << 15) | ((nsl >> 1) << 18), rso = ((rsl & 1) << 15) | ((rsl >> 1) << 18);
            { uint32_t z_; asm volatile("ld.volatile.shared.u32 %0,[%1];" : "=r"(z_) : "r"(sb + OFF_BAR + 248) : "memory"); if (z_ == 0x12345678u) __trap(); }
            int tclk; asm volatile("mov.u32 %0, %%clock;" : "=r"(tclk)::"memory");
            char* po0 = SCR + (mo0 + nso); char* po1 = SCR + ((mo0 ^ 0x1000u) + nso);
            const char* ma = SCR + (mi0 + nso); const char* mb = SCR + ((mi0 ^ 0x3000u) + nso);
            asm volatile("" : "+l"(po0), "+l"(po1), "+l"(ma), "+l"(mb));
            if (red) {
                const uint32_t flip = ph;
                const char* b = SCR + (pbase + ((uint32_t)p << 20));
                { int c; do { asm volatile("mov.u32 %0, %%clock;" : "=r"(c)::"memory"); } while (c - tclk < d1); }
                auto finish = [&](const uint4& v0, const uint4& v1, const uint4& v2, const uint4& v3) {
                    auto f = [](uint32_t w) { return __uint_as_float(w); };
                    const float a0 = (f(v0.x) + f(v1.x)) + (f(v2.x) + f(v3.x));
                    const float a1 = (f(v0.y) + f(v1.y)) + (f(v2.y) + f(v3.y));
                    const float a2 = (f(v0.z) + f(v1.z)) + (f(v2.z) + f(v3.z));
                    const float a3 = (f(v0.w) + f(v1.w)) + (f(v2.w) + f(v3.w));
                    const bool up = lane & 16;
                    float k0f = up ? a1 : a0, k1f = up ? a3 : a2;
                    k0f += __shfl_xor_sync(~0u, up ? a0 : a1, 16); k1f += __shfl_xor_sync(~0u, up ? a2 : a3, 16);
                    k0f += __shfl_xor_sync(~0u, k0f, 8); k1f += __shfl_xor_sync(~0u, k1f, 8);
                    k0f += __shfl_xor_sync(~0u, k0f, 4); k1f += __shfl_xor_sync(~0u, k1f, 4);
                    const uint32_t wv = pack_bf16(k0f, k1f);
                    if ((lane & 12) == 0) { stg_relaxed32(po0, wv); stg_relaxed32(po1, wv); }
                };
                uint4 v0 = ldg_relaxed128(b), v1 = ldg_relaxed128(b + 256), v2 = ldg_relaxed128(b + 512), v3 = ldg_relaxed128(b + 768);
                int gd = 0;
                while (true) {
                    const uint32_t k0 = tag_and(v0, flip), k1 = tag_and(v1, flip), k2 = tag_and(v2, flip), k3 = tag_and(v3, flip);
                    if (__all_sync(~0u, (k0 & k1 & k2 & k3) & 1)) break;
                    if (!(k0 & 1)) v0 = ldg_relaxed128(b);
                    if (!(k1 & 1)) v1 = ldg_relaxed128(b + 256);
                    if (!(k2 & 1)) v2 = ldg_relaxed128(b + 512);
                    if (!(k3 & 1)) v3 = ldg_relaxed128(b + 768);
                    if (++gd > SPIN_LIMIT) __trap();
                }
                finish(v0, v1, v2, v3);
            }
            if (red) bar_arrive(NB_G2, 384);
            else { int c; do { asm volatile("mov.u32 %0, %%clock;" : "=r"(c)::"memory"); } while (c - tclk < d1 + 500); bar_arrive(NB_G2, 384); }
            if (red) { asm volatile("mov.u32 %0, %%clock;" : "=r"(tclk)::"memory"); int c; do { asm volatile("mov.u32 %0, %%clock;" : "=r"(c)::"memory"); } while (c - tclk < d2); }
            else { int c; do { asm volatile("mov.u32 %0, %%clock;" : "=r"(c)::"memory"); } while (c - tclk < d1 + DNR + d2); }
            {
                uint4 v0 = ldg_relaxed128(ma), v1 = ldg_relaxed128(ma + 2048), v2 = ldg_relaxed128(mb), v3 = ldg_relaxed128(mb + 2048), v4 = ldg_relaxed128(ma + 0x4000);
                const uint32_t md = sb + OFF_MEMS + ht * 16;
                int gd = 0;
                while (true) {
                    sts128(md, v0); sts128(md + 2048, v1); sts128(md + 4096, v2); sts128(md + 6144, v3); sts128(md + 8192, v4);
                    const bool k0 = sent_ok(v0), k1 = sent_ok(v1), k2 = sent_ok(v2), k3 = sent_ok(v3), k4 = sent_ok(v4);
                    if (k0 & k1 & k2 & k3 & k4) break;
                    if (!k0) v0 = ldg_relaxed128(ma);
                    if (!k1) v1 = ldg_relaxed128(ma + 2048);
                    if (!k2) v2 = ldg_relaxed128(mb);
                    if (!k3) v3 = ldg_relaxed128(mb + 2048);
                    if (!k4) v4 = ldg_relaxed128(ma + 0x4000);
                    if (++gd > SPIN_LIMIT) __trap();
                }
                bar_arrive(NB_MEM, 384);
            }
            if (red && (lane & 12) == 0) { stg_relaxed32(SCR + (mo0 + rso), ~0u); stg_relaxed32(SCR + ((mo0 ^ 0x1000u) + rso), ~0u); }
        }
        cluster_arrive(); cluster_wait();
    }
}

DEVI void bulk_g2s(uint32_t dst, const void* src, uint32_t bytes, uint32_t bar) {
    asm volatile("cp.async.bulk.shared::cluster.global.mbarrier::complete_tx::bytes [%0],[%1],%2,[%3];" ::"r"(dst), "l"(src), "r"(bytes), "r"(bar) : "memory");
}
DEVI void attn_warp(uint32_t img, uint32_t ost, int mi, int lane, __nv_bfloat16* orow  ) {
    const int li = lane >> 3, lr = lane & 7, g = lane >> 2, t = lane & 3;
    float sc[5][4];
#pragma unroll
    for (int nj = 0; nj < 5; nj++) { sc[nj][0] = sc[nj][1] = sc[nj][2] = sc[nj][3] = 0.f; }
#pragma unroll
    for (int hf = 0; hf < 2; hf++) {
#pragma unroll
        for (int kp = 0; kp < 2; kp++) {
            uint32_t a0[4], a1[4];
            const uint32_t qrow = img + hf * 4096 + (16 * mi + (li & 1) * 8 + lr) * 128;
            ldsm4(a0, qrow + (((4 * kp + (li >> 1)) ^ lr) << 4));
            ldsm4(a1, qrow + (((4 * kp + 2 + (li >> 1)) ^ lr) << 4));
#pragma unroll
            for (int nj = 0; nj < 5; nj++) {
                uint32_t b[4];
                ldsm4(b, img + 8192 + hf * 5120 + (8 * nj + lr) * 128 + (((4 * kp + li) ^ lr) << 4));
                mma16816(sc[nj], a0[0], a0[1], a0[2], a0[3], b[0], b[1]);
                mma16816(sc[nj], a1[0], a1[1], a1[2], a1[3], b[2], b[3]);
            }
        }
    }
    const float sl2 = 0.08838834764831845f * 1.4426950408889634f;
    const int i0 = 16 * mi + g, i1 = i0 + 8;
    float m0 = -1e30f, m1 = -1e30f;
#pragma unroll
    for (int nj = 0; nj < 5; nj++) {
        const int key = 8 * nj + 2 * t;
        if (nj < 4) {
            if (key > i0) sc[nj][0] = -1e30f;
            if (key + 1 > i0) sc[nj][1] = -1e30f;
            if (key > i1) sc[nj][2] = -1e30f;
            if (key + 1 > i1) sc[nj][3] = -1e30f;
        }
        m0 = fmaxf(m0, fmaxf(sc[nj][0], sc[nj][1])); m1 = fmaxf(m1, fmaxf(sc[nj][2], sc[nj][3]));
    }
    m0 = fmaxf(m0, __shfl_xor_sync(~0u, m0, 1)); m1 = fmaxf(m1, __shfl_xor_sync(~0u, m1, 1));
    m0 = fmaxf(m0, __shfl_xor_sync(~0u, m0, 2)); m1 = fmaxf(m1, __shfl_xor_sync(~0u, m1, 2));
    m0 *= sl2; m1 *= sl2;
    float u0 = 0.f, u1 = 0.f;
#pragma unroll
    for (int nj = 0; nj < 5; nj++) {
        sc[nj][0] = ex2(fmaf(sc[nj][0], sl2, -m0)); sc[nj][1] = ex2(fmaf(sc[nj][1], sl2, -m0)); u0 += sc[nj][0] + sc[nj][1];
        sc[nj][2] = ex2(fmaf(sc[nj][2], sl2, -m1)); sc[nj][3] = ex2(fmaf(sc[nj][3], sl2, -m1)); u1 += sc[nj][2] + sc[nj][3];
    }
    u0 += __shfl_xor_sync(~0u, u0, 1); u1 += __shfl_xor_sync(~0u, u1, 1);
    u0 += __shfl_xor_sync(~0u, u0, 2); u1 += __shfl_xor_sync(~0u, u1, 2);
    u0 = __fdividef(1.f, u0); u1 = __fdividef(1.f, u1);
    uint32_t pa[10];
#pragma unroll
    for (int nj = 0; nj < 5; nj++) { pa[2 * nj] = pack_bf16(sc[nj][0] * u0, sc[nj][1] * u0); pa[2 * nj + 1] = pack_bf16(sc[nj][2] * u1, sc[nj][3] * u1); }
    const uint32_t vimg = img + 8192 + 10240;
#pragma unroll
    for (int dg = 0; dg < 8; dg++) {
        const int c16 = 2 * dg + (li >> 1), c16b = 2 * dg + (li & 1);
        const uint32_t vb = vimg + ((li & 1) * 8 + lr) * 256 + (((c16 & 8) | ((c16 ^ lr) & 7)) << 4);
        uint32_t v0[4], v1[4], v2[2];
        ldsm4t(v0, vb); ldsm4t(v1, vb + 16 * 256);
        ldsm2t(v2, vimg + (32 + lr) * 256 + (((c16b & 8) | ((c16b ^ lr) & 7)) << 4));
        float o0[4] = {0.f, 0.f, 0.f, 0.f}, o1[4] = {0.f, 0.f, 0.f, 0.f};
        mma16816(o0, pa[0], pa[1], pa[2], pa[3], v0[0], v0[1]);
        mma16816(o1, pa[0], pa[1], pa[2], pa[3], v0[2], v0[3]);
        mma16816(o0, pa[4], pa[5], pa[6], pa[7], v1[0], v1[1]);
        mma16816(o1, pa[4], pa[5], pa[6], pa[7], v1[2], v1[3]);
        mma1688(o0, pa[8], pa[9], v2[0]);
        mma1688(o1, pa[8], pa[9], v2[1]);
        stsm4(ost + ((li & 1) * 8 + lr) * 272 + (2 * dg + (li >> 1)) * 16,
              pack_bf16(o0[0], o0[1]), pack_bf16(o0[2], o0[3]), pack_bf16(o1[0], o1[1]), pack_bf16(o1[2], o1[3]));
    }
    __syncwarp();
#pragma unroll
    for (int q = 0; q < 8; q++) {
        const int row = 2 * q + (lane >> 4), ch = lane & 15;
        *(uint4*)(orow + (size_t)row * 4096 + ch * 8) = lds128(ost + row * 272 + ch * 16);
    }
    __syncwarp();
}

DEVI void wgmma_ss_n64_tb(float* d, uint64_t da, uint64_t db) {
    asm volatile("wgmma.mma_async.sync.aligned.m64n64k16.f32.bf16.bf16 "
        "{%0,%1,%2,%3,%4,%5,%6,%7,%8,%9,%10,%11,%12,%13,%14,%15,%16,%17,%18,%19,%20,%21,%22,%23,%24,%25,%26,%27,%28,%29,%30,%31},%32,%33,1,1,1,0,1;"
        : "+f"(d[0]), "+f"(d[1]), "+f"(d[2]), "+f"(d[3]), "+f"(d[4]), "+f"(d[5]), "+f"(d[6]), "+f"(d[7]), "+f"(d[8]), "+f"(d[9]), "+f"(d[10]), "+f"(d[11]), "+f"(d[12]), "+f"(d[13]), "+f"(d[14]), "+f"(d[15]),
          "+f"(d[16]), "+f"(d[17]), "+f"(d[18]), "+f"(d[19]), "+f"(d[20]), "+f"(d[21]), "+f"(d[22]), "+f"(d[23]), "+f"(d[24]), "+f"(d[25]), "+f"(d[26]), "+f"(d[27]), "+f"(d[28]), "+f"(d[29]), "+f"(d[30]), "+f"(d[31])
        : "l"(da), "l"(db));
}
template <int ACC> DEVI void wgmma_ss_n128_tb(float* d, uint64_t da, uint64_t db) {
    asm volatile("wgmma.mma_async.sync.aligned.m64n128k16.f32.bf16.bf16 "
        "{%0,%1,%2,%3,%4,%5,%6,%7,%8,%9,%10,%11,%12,%13,%14,%15,%16,%17,%18,%19,%20,%21,%22,%23,%24,%25,%26,%27,%28,%29,%30,%31,"
        "%32,%33,%34,%35,%36,%37,%38,%39,%40,%41,%42,%43,%44,%45,%46,%47,%48,%49,%50,%51,%52,%53,%54,%55,%56,%57,%58,%59,%60,%61,%62,%63},%64,%65,%66,1,1,0,1;"
        : "+f"(d[0]), "+f"(d[1]), "+f"(d[2]), "+f"(d[3]), "+f"(d[4]), "+f"(d[5]), "+f"(d[6]), "+f"(d[7]), "+f"(d[8]), "+f"(d[9]), "+f"(d[10]), "+f"(d[11]), "+f"(d[12]), "+f"(d[13]), "+f"(d[14]), "+f"(d[15]),
          "+f"(d[16]), "+f"(d[17]), "+f"(d[18]), "+f"(d[19]), "+f"(d[20]), "+f"(d[21]), "+f"(d[22]), "+f"(d[23]), "+f"(d[24]), "+f"(d[25]), "+f"(d[26]), "+f"(d[27]), "+f"(d[28]), "+f"(d[29]), "+f"(d[30]), "+f"(d[31]),
          "+f"(d[32]), "+f"(d[33]), "+f"(d[34]), "+f"(d[35]), "+f"(d[36]), "+f"(d[37]), "+f"(d[38]), "+f"(d[39]), "+f"(d[40]), "+f"(d[41]), "+f"(d[42]), "+f"(d[43]), "+f"(d[44]), "+f"(d[45]), "+f"(d[46]), "+f"(d[47]),
          "+f"(d[48]), "+f"(d[49]), "+f"(d[50]), "+f"(d[51]), "+f"(d[52]), "+f"(d[53]), "+f"(d[54]), "+f"(d[55]), "+f"(d[56]), "+f"(d[57]), "+f"(d[58]), "+f"(d[59]), "+f"(d[60]), "+f"(d[61]), "+f"(d[62]), "+f"(d[63])
        : "l"(da), "l"(db), "n"(ACC));
}

constexpr int K2_THREADS = 288;
constexpr int GB_STAGES = NST;
constexpr uint32_t GB_STAGE_BYTES = 16384 + 16384;
constexpr uint32_t K2_BAR = 6 * GB_STAGE_BYTES;
constexpr uint32_t K2_SMEM = K2_BAR + 256 + 1024;
constexpr int N_B = 80, N_A = 504,        N_G = 12 * 5 + (5 << L12) + (5 << L13) + (5 << L14) + (5 << L16) + (5 << L17);
constexpr int TICKET_END = 1 << 20, TICKET_A = 1 << 16, TICKET_G = 1 << 12;
DEVI void g_item(int k, int& rt, int& lsp, int& idx) {
    if (k < 60) { rt = k / 5; lsp = 0; idx = k % 5; return; }
    k -= 60;
    if (k < (5 << L12)) { rt = 12; lsp = L12; idx = k; return; }
    k -= 5 << L12;
    if (k < (5 << L13)) { rt = 13; lsp = L13; idx = k; return; }
    k -= 5 << L13;
    if (k < (5 << L14)) { rt = 14; lsp = L14; idx = k; return; }
    k -= 5 << L14;
    if (k < (5 << L16)) { rt = 16; lsp = L16; idx = k; return; }
    rt = 17; lsp = L17; idx = k - (5 << L16);
}
constexpr uint32_t CB_RAWK = 0, CB_RAWV = 33024, CB_U = 66048, CB_U_CH = 5136, CB_KC = CB_U + 8 * CB_U_CH + 64  , CB_KC_CH = 8576, CB_Y_CH = 4112;
static_assert(CB_KC % 128 == 64 || CB_KC % 16 == 0, "alignment");
static_assert(CB_KC + 8 * CB_KC_CH <= K2_BAR, "B item smem");

__device__ float4 g_part[((5 << L12) + (5 << L13) + (5 << L14) + (5 << L16) + (5 << L17)) * 4096];

struct K2Params { const __nv_bfloat16 *shk, *ssk, *ssD; __nv_bfloat16* out; };

DEVI uint32_t ld_acquire(const unsigned* p) { uint32_t v; asm volatile("ld.acquire.gpu.global.u32 %0,[%1];" : "=r"(v) : "l"(p) : "memory"); return v; }
DEVI void wait_count(const unsigned* p, unsigned target) {
    int gd = 0;
    while (ldg_relaxed32(p) < target) { __nanosleep(40); if (++gd > SPIN_LIMIT) __trap(); }
    (void)ld_acquire(p);
}
DEVI uint32_t hmul2(uint32_t a, uint32_t b) { uint32_t r; asm("mul.rn.bf16x2 %0,%1,%2;" : "=r"(r) : "r"(a), "r"(b)); return r; }
DEVI uint32_t hadd2(uint32_t a, uint32_t b) { uint32_t r; asm("add.rn.bf16x2 %0,%1,%2;" : "=r"(r) : "r"(a), "r"(b)); return r; }
DEVI uint32_t lds32(uint32_t a) { uint32_t v; asm volatile("ld.shared.u32 %0,[%1];" : "=r"(v) : "r"(a) : "memory"); return v; }

__global__ void __launch_bounds__(K2_THREADS, 1)
k2_work(const __grid_constant__ CUtensorMap tmO, const __grid_constant__ CUtensorMap tmO64, const __grid_constant__ CUtensorMap tmWo, const __grid_constant__ CUtensorMap tmBq,
        const __grid_constant__ CUtensorMap tmBk, const __grid_constant__ CUtensorMap tmBv, K2Params prm)
{
    extern __shared__ unsigned char smem_raw[];
    const uint32_t sb = (smem_u32(smem_raw) + 1023u) & ~1023u;
    const uint32_t full = sb + K2_BAR, empty = full + 8 * GB_STAGES, ldbar = empty + 8 * GB_STAGES, qbar = ldbar + 8, abar = qbar + 8, s_item = abar + 32, s_last = s_item + 8;
    const int tid = threadIdx.x, warp = tid >> 5, lane = tid & 31;
    if (tid == 0) {
        for (int i = 0; i < GB_STAGES; i++) { mbar_init(full + 8 * i, 1); mbar_init(empty + 8 * i, 2); }
        mbar_init(ldbar, 1); mbar_init(qbar, 1);
        for (int i = 0; i < 4; i++) mbar_init(abar + 8 * i, 1);
        asm volatile("fence.mbarrier_init.release.cluster;" ::: "memory");
        fence_async_smem();
    }
    bool a_only = false;
    if (tid == 256) a_only = atomicAdd(&g_ctl.role, 1u) < NA_RES;
    auto draw = [&]() -> int {
        int gd = 0;
        while (true) {
            const unsigned ia = ldg_relaxed32(&g_ctl.qa), ig = ldg_relaxed32(&g_ctl.qg), ib = ldg_relaxed32(&g_ctl.qb);
            int rt = 0, lsp, idx;
            g_item((int)min(ig, (unsigned)N_G - 1), rt, lsp, idx);
            const unsigned sa = min(ia, (unsigned)N_A - 1) >> 3;
            const unsigned fa = ldg_relaxed32(&g_ctl.seg[sa]), fp = ldg_relaxed32(&g_ctl.seg[sa > 0 ? sa - 1 : 0]), fg = ldg_relaxed32(&g_ctl.ox[rt]);
            if (ia < N_A && fa >= K1_CTAS) { const unsigned i = atomicAdd(&g_ctl.qa, 1u); if (i < N_A) return TICKET_A + (int)i; continue; }
            if (ig < N_G && !(a_only && ia < N_A) && (fg >= (rt < 16 ? 32u : (rt == 16 ? 16u : 40u)) || ia >= N_A)) { const unsigned i = atomicAdd(&g_ctl.qg, 1u); if (i < N_G) return TICKET_G + (int)i; continue; }
            if (ib < N_B) { const unsigned i = atomicAdd(&g_ctl.qb, 1u); if (i < N_B) return (int)i; continue; }
            if (ABLOCK && ia < N_A && fp >= K1_CTAS) { const unsigned i = atomicAdd(&g_ctl.qa, 1u); if (i < N_A) return TICKET_A + (int)i; continue; }
            if (ia >= N_A && ig >= N_G) return TICKET_END;
            __nanosleep(DSLEEP);
            if (++gd > SPIN_LIMIT) __trap();
        }
    };
    __syncthreads();
    if (tid == 256) sts32(s_item, draw());
    __syncthreads();
    uint32_t ld_ph = 0, q_ph = 0, a_ph = 0, g_it = 0;
    const int li = lane >> 3, lr = lane & 7, g = lane >> 2, t = lane & 3;

    while (true) {
        const int item = (int)lds32(s_item);
        __syncthreads();
        if (item == TICKET_END) break;
        int type, a0 = 0, a1 = 0, lsp = 0;
        if (item >= TICKET_A) { type = 1; a0 = (item - TICKET_A) >> 5; a1 = (item - TICKET_A) & 31; }
        else if (item >= TICKET_G) { g_item(item - TICKET_G, a0, lsp, a1); type = lsp ? 3 : 2; }
        else { type = 0; a0 = item; }
        if (type == 0) {
            const int c0 = a0 * 8;
            if (tid == 256) {
                mbar_expect(ldbar, 2 * 32768 + 8 * 4096);
                for (int b = 0; b < 8; b++) { tma2d(sb + CB_RAWK + b * 4096, &tmBk, c0, b * 256, ldbar); tma2d(sb + CB_RAWV + b * 4096, &tmBv, c0, b * 256, ldbar); }
                for (int c = 0; c < 8; c++) bulk_g2s(sb + CB_KC + c * CB_KC_CH + 128, prm.ssk + (size_t)(c0 + c) * S_, 4096, ldbar);
            }
            if (warp < 8) {
                if (lane < 8) sts128(sb + CB_KC + warp * CB_KC_CH + lane * 16, make_uint4(0, 0, 0, 0));
                for (int i = lane; i < 64; i += 32) sts128(sb + CB_U + warp * CB_U_CH + i * 16, make_uint4(0, 0, 0, 0));
                const uint2 wa = *(const uint2*)(prm.shk + (c0 + 2 * t) * 4), wb = *(const uint2*)(prm.shk + (c0 + 2 * t + 1) * 4);
                const uint32_t w0 = __byte_perm(wa.x, wb.x, 0x5410), w1 = __byte_perm(wa.x, wb.x, 0x7632), w2 = __byte_perm(wa.y, wb.y, 0x5410), w3 = __byte_perm(wa.y, wb.y, 0x7632);
                mbar_wait(ldbar, ld_ph);
                {
                    const uint32_t c0a = sb + CB_KC + warp * CB_KC_CH, c1a = c0a + 4288;
                    __syncwarp();
                    for (int i = lane; i < 264; i += 32) {
                        const uint4 x = lds128(c0a + i * 16);
                        const uint32_t nx = (i < 263) ? lds32(c0a + i * 16 + 16) : 0u;
                        sts128(c1a + i * 16, make_uint4(__byte_perm(x.x, x.y, 0x5432), __byte_perm(x.y, x.z, 0x5432), __byte_perm(x.z, x.w, 0x5432), __byte_perm(x.w, nx, 0x5432)));
                    }
                }
                for (int it = 0; it < 8; it++) {
                    uint32_t r[4];
#pragma unroll
                    for (int m = 0; m < 4; m++) {
                        const int T = (warp * 8 + it) * 32 + m * 8, tm = T + 7 - g;
                        const uint32_t ka = sb + CB_RAWK + tm * 16 + t * 4;
                        const uint32_t k0 = lds32(ka), k1 = tm >= 1 ? lds32(ka - 16) : 0u, k2 = tm >= 2 ? lds32(ka - 32) : 0u, k3 = tm >= 3 ? lds32(ka - 48) : 0u;
                        const uint32_t vv = lds32(sb + CB_RAWV + tm * 16 + t * 4);
                        uint32_t acc = hmul2(k3, w3);
                        acc = hadd2(acc, hmul2(k2, w2));
                        acc = hadd2(acc, hmul2(k1, w1));
                        acc = hadd2(acc, hmul2(k0, w0));
                        r[m] = hmul2(acc, vv);
                    }
                    const int T0 = (warp * 8 + it) * 32 + li * 8, jc = 8 + (T0 >> 6), ch = 2 * ((T0 >> 4) & 3) + 1 - ((T0 >> 3) & 1);
                    stsm4t(sb + CB_U + lr * CB_U_CH + jc * 128 + ((ch ^ (jc & 7)) << 4), r[0], r[1], r[2], r[3]);
                }
            }
            __syncthreads();
            if (tid == 256) {
                fence_async_smem();
                mbar_expect(qbar, 32768);
                for (int b = 0; b < 8; b++) tma2d(sb + CB_RAWK + b * 4096, &tmBq, c0, b * 256, qbar);
            }
            if (warp < 8) {
                float acc[4][4][4];
#pragma unroll
                for (int a = 0; a < 4; a++)
#pragma unroll
                    for (int b = 0; b < 4; b++) { acc[a][b][0] = acc[a][b][1] = acc[a][b][2] = acc[a][b][3] = 0.f; }
                const uint32_t kw0 = sb + CB_KC + warp * CB_KC_CH + ((g & 1) ? 0u : 4288u - 2u) + (uint32_t)(64 - 15 + g + 2 * t) * 2;
                const uint32_t ub = sb + CB_U + warp * CB_U_CH;
                uint32_t wv[15];
#pragma unroll
                for (int e = 0; e < 15; e++) wv[e] = lds32(kw0 + (uint32_t)(8 * (e - 6)) * 2);
                auto lag_phase = [&](auto q0c) {
                    constexpr int q0 = decltype(q0c)::value;
#pragma unroll 1
                    for (int l = 8 * q0; l < 8 * q0 + 8; l++) {
                        uint32_t wn[8];
                        const int ln = min(l + 1, 31);
#pragma unroll
                        for (int e = 0; e < 8; e++) wn[e] = lds32(kw0 + (uint32_t)(64 * ln + 8 * (e + 1)) * 2);
                        uint32_t b[2][4];
                        {
                            const int jc = 8 + 8 * q0 + lr - l;
                            ldsm4(b[0], ub + jc * 128 + ((li ^ (jc & 7)) << 4));
                        }
#pragma unroll
                        for (int u = 0; u < 2 * (4 - q0); u++) {
                            const int ni = q0 + (u >> 1), kp = u & 1;
                            if (u + 1 < 2 * (4 - q0)) {
                                const int jn = 8 + 8 * (q0 + ((u + 1) >> 1)) + lr - l;
                                ldsm4(b[(u + 1) & 1], ub + jn * 128 + (((4 * ((u + 1) & 1) + li) ^ (jn & 7)) << 4));
                            }
#pragma unroll
                            for (int kq = 0; kq < 2; kq++) {
                                const int kk = 2 * kp + kq;
#pragma unroll
                                for (int mi = 0; mi < 4; mi++) {
                                    const int e = 6 + 2 * (mi - kk);
                                    mma16816(acc[mi][ni], wv[e], wv[e + 1], wv[e + 1], wv[e + 2], b[u & 1][2 * kq], b[u & 1][2 * kq + 1]);
                                }
                            }
                        }
#pragma unroll
                        for (int e = 0; e < 7; e++) wv[e] = wv[e + 8];
#pragma unroll
                        for (int e = 0; e < 8; e++) wv[7 + e] = wn[e];
                    }
                };
                lag_phase(std::integral_constant<int, 0>{}); lag_phase(std::integral_constant<int, 1>{});
                lag_phase(std::integral_constant<int, 2>{}); lag_phase(std::integral_constant<int, 3>{});
                const uint32_t yb = sb + CB_RAWV + warp * CB_Y_CH;
#pragma unroll
                for (int mi = 0; mi < 4; mi++)
#pragma unroll
                    for (int np = 0; np < 2; np++) {
                        const int i = 8 * (2 * np + (li >> 1)) + lr;
                        stsm4t(yb + i * 128 + (((2 * mi + (li & 1)) ^ (i & 7)) << 4),
                               pack_bf16(acc[mi][2 * np][0], acc[mi][2 * np][1]), pack_bf16(acc[mi][2 * np][2], acc[mi][2 * np][3]),
                               pack_bf16(acc[mi][2 * np + 1][0], acc[mi][2 * np + 1][1]), pack_bf16(acc[mi][2 * np + 1][2], acc[mi][2 * np + 1][3]));
                    }
            }
            __syncthreads();
            if (warp < 8) {
                const uint32_t dw = __byte_perm((uint32_t)__bfloat16_as_ushort(prm.ssD[c0 + 2 * t]), (uint32_t)__bfloat16_as_ushort(prm.ssD[c0 + 2 * t + 1]), 0x5410);
                mbar_wait(qbar, q_ph);
                for (int it = 0; it < 8; it++) {
                    const int T0 = (warp * 8 + it) * 32 + li * 8, i = T0 >> 6, qc = (T0 >> 3) & 7;
                    uint32_t y[4], u[4];
                    ldsm4t(y, sb + CB_RAWV + lr * CB_Y_CH + i * 128 + ((qc ^ (i & 7)) << 4));
                    const int jc = 8 + i, ch = 2 * ((T0 >> 4) & 3) + 1 - ((T0 >> 3) & 1);
                    ldsm4t(u, sb + CB_U + lr * CB_U_CH + jc * 128 + ((ch ^ (jc & 7)) << 4));
#pragma unroll
                    for (int m = 0; m < 4; m++) {
                        const int tm = (warp * 8 + it) * 32 + m * 8 + g;
                        const uint32_t kv = __shfl_sync(~0u, u[m], (7 - g) * 4 + t);
                        const uint32_t y2 = hadd2(y[m], hmul2(kv, dw));
                        const uint32_t qq = lds32(sb + CB_RAWK + tm * 16 + t * 4);
                        *(uint32_t*)(prm.out + (size_t)tm * 1280 + 640 + c0 + 2 * t) = hmul2(qq, y2);
                    }
                }
            }
            ld_ph ^= 1; q_ph ^= 1;
        } else if (type == 1) {
            const int sg = 4 * a0 + (a1 >> 3), hg = a1 & 7;
            if (tid == 256) {
                wait_count(&g_ctl.seg[sg], K1_CTAS);
                asm volatile("fence.proxy.async;" ::: "memory");
                for (int i = 0; i < 4; i++) {
                    if (ASTAG && i >= ASTAG) mbar_wait(abar + 8 * (i - ASTAG), a_ph);
                    mbar_expect(abar + 8 * i, QKV_IMG);
                    bulk_g2s(sb + i * QKV_IMG, g_qkv + (size_t)(sg * NH + 4 * hg + i) * QKV_IMG, QKV_IMG, abar + 8 * i);
                }
            }
            if (warp < 8) {
                mbar_wait(abar + 8 * (warp >> 1), a_ph);
                const int hh = 4 * hg + (warp >> 1), mi = warp & 1;
                attn_warp(sb + (warp >> 1) * QKV_IMG, sb + 4 * QKV_IMG + warp * 16 * 272, mi, lane, g_ox + (size_t)(sg * 32 + 16 * mi) * 4096 + hh * 128);
            }
            __syncthreads();
            if (tid == 0) asm volatile("red.release.gpu.global.add.u32 [%0],1;" ::"l"(&g_ctl.ox[a0 < 15 ? a0 : 16 + (a1 >> 4)]) : "memory");
            a_ph ^= 1;
        } else {
            const bool half = a0 >= 16;
            const uint32_t stage_bytes = half ? 8192 + 16384 : GB_STAGE_BYTES;
            const int row0 = half ? 1920 + (a0 - 16) * 64 : a0 * 128;
            const CUtensorMap* tmA = half ? &tmO64 : &tmO;
            const int rt = a0, nt = a1 >> lsp, nkt = 64 >> lsp, kt0 = (a1 & ((1 << lsp) - 1)) * nkt;
            if (warp == 8) {
                if (lane == 0) {
                    const int npre = min(nkt, GB_STAGES);
                    for (int kt = 0; kt < npre; kt++) {
                        const uint32_t it = g_it + kt, st = it % GB_STAGES, rnd = it / GB_STAGES;
                        if (rnd > 0) mbar_wait(empty + 8 * st, (rnd - 1) & 1);
                        mbar_expect(full + 8 * st, stage_bytes);
                        const uint32_t a = sb + st * GB_STAGE_BYTES;
                        tma2d(a + 16384, &tmWo, nt * 128, (kt0 + kt) * 64, full + 8 * st);
                        tma2d(a + 16384 + 8192, &tmWo, nt * 128 + 64, (kt0 + kt) * 64, full + 8 * st);
                    }
                    wait_count(&g_ctl.ox[rt], rt < 16 ? 32 : (rt == 16 ? 16 : 40));
                    asm volatile("fence.proxy.async;" ::: "memory");
                    for (int kt = 0; kt < npre; kt++) {
                        const uint32_t st = (g_it + kt) % GB_STAGES;
                        tma2d(sb + st * GB_STAGE_BYTES, tmA, (kt0 + kt) * 64, row0, full + 8 * st);
                    }
                    for (int kt = npre; kt < nkt; kt++) {
                        const uint32_t it = g_it + kt, st = it % GB_STAGES, rnd = it / GB_STAGES;
                        mbar_wait(empty + 8 * st, (rnd - 1) & 1);
                        mbar_expect(full + 8 * st, stage_bytes);
                        const uint32_t a = sb + st * GB_STAGE_BYTES;
                        tma2d(a, tmA, (kt0 + kt) * 64, row0, full + 8 * st);
                        tma2d(a + 16384, &tmWo, nt * 128, (kt0 + kt) * 64, full + 8 * st);
                        tma2d(a + 16384 + 8192, &tmWo, nt * 128 + 64, (kt0 + kt) * 64, full + 8 * st);
                    }
                }
                __syncwarp();
            } else if (half) {
                const int wg = warp >> 2;
                float d[32];
#pragma unroll
                for (int i = 0; i < 32; i++) d[i] = 0.f;
                for (int kt = 0; kt < nkt; kt++) {
                    const uint32_t it = g_it + kt, st = it % GB_STAGES, rnd = it / GB_STAGES;
                    mbar_wait(full + 8 * st, rnd & 1);
                    const uint32_t a = sb + st * GB_STAGE_BYTES, b = sb + st * GB_STAGE_BYTES + 16384 + wg * 8192;
                    const uint64_t da = (uint64_t)((a & 0x3FFFF) >> 4) | (1ull << 16) | (64ull << 32) | (1ull << 62);
                    const uint64_t db = (uint64_t)((b & 0x3FFFF) >> 4) | (512ull << 16) | (64ull << 32) | (1ull << 62);
                    wg_fence();
#pragma unroll
                    for (int k = 0; k < 4; k++) wgmma_ss_n64_tb(d, da + 2 * k, db + 128 * k);
                    wg_commit();
                    wg_wait<1>();
                    if (kt > 0 && (tid & 127) == 0) mbar_arrive(empty + 8 * ((it - 1) % GB_STAGES));
                }
                wg_wait<0>();
                if ((tid & 127) == 0) mbar_arrive(empty + 8 * ((g_it + nkt - 1) % GB_STAGES));
                float4* ps = g_part + (size_t)(item - TICKET_G - 60) * 4096 + tid;
#pragma unroll
                for (int n = 0; n < 8; n++) __stcg(ps + n * 256, make_float4(d[4 * n], d[4 * n + 1], d[4 * n + 2], d[4 * n + 3]));
            } else {
                const int wg = warp >> 2;
                float d[64];
#pragma unroll
                for (int i = 0; i < 64; i++) d[i] = 0.f;
                for (int kt = 0; kt < nkt; kt++) {
                    const uint32_t it = g_it + kt, st = it % GB_STAGES, rnd = it / GB_STAGES;
                    mbar_wait(full + 8 * st, rnd & 1);
                    const uint32_t a = sb + st * GB_STAGE_BYTES + wg * 8192, b = sb + st * GB_STAGE_BYTES + 16384;
                    const uint64_t da = (uint64_t)((a & 0x3FFFF) >> 4) | (1ull << 16) | (64ull << 32) | (1ull << 62);
                    const uint64_t db = (uint64_t)((b & 0x3FFFF) >> 4) | (512ull << 16) | (64ull << 32) | (1ull << 62);
                    wg_fence();
#pragma unroll
                    for (int k = 0; k < 4; k++) wgmma_ss_n128_tb<1>(d, da + 2 * k, db + 128 * k);
                    wg_commit();
                    wg_wait<1>();
                    if (kt > 0 && (tid & 127) == 0) mbar_arrive(empty + 8 * ((it - 1) % GB_STAGES));
                }
                wg_wait<0>();
                if ((tid & 127) == 0) mbar_arrive(empty + 8 * ((g_it + nkt - 1) % GB_STAGES));
                const int w = warp & 3, r0 = wg * 64 + w * 16 + g;
                if (type == 2) {
#pragma unroll
                    for (int n = 0; n < 16; n++) {
                        const int col = nt * 128 + 8 * n + 2 * t;
                        *(uint32_t*)(prm.out + (size_t)(rt * 128 + r0) * 1280 + col) = pack_bf16(d[4 * n], d[4 * n + 1]);
                        *(uint32_t*)(prm.out + (size_t)(rt * 128 + r0 + 8) * 1280 + col) = pack_bf16(d[4 * n + 2], d[4 * n + 3]);
                    }
                } else {
                    float4* ps = g_part + (size_t)(item - TICKET_G - 60) * 4096 + tid;
#pragma unroll
                    for (int n = 0; n < 16; n++) __stcg(ps + n * 256, make_float4(d[4 * n], d[4 * n + 1], d[4 * n + 2], d[4 * n + 3]));
                }
            }
            g_it += nkt;
            if (type == 3) {
                const int nsp = 1 << lsp, kc = a1 & (nsp - 1);
                const bool shared_fin = (rt >= SHARED_FIN);
                unsigned* cnt = &g_ctl.cnt[(rt - 12) * 5 + nt];
                __syncthreads();
                if (tid == 0) {
                    if (shared_fin) { asm volatile("red.release.gpu.global.add.u32 [%0],1;" ::"l"(cnt) : "memory"); wait_count(cnt, nsp); }
                    else { unsigned old; asm volatile("atom.acq_rel.gpu.global.add.u32 %0,[%1],1;" : "=r"(old) : "l"(cnt) : "memory"); sts32(s_last + 4, old); }
                }
                __syncthreads();
                if (half) {
                    const int per = 16 >> lsp;
                    const float4* ps = g_part + (size_t)(item - TICKET_G - 60 - kc) * 4096 + tid;
                    for (int q = 0; q < per; q++) {
                        const int sl = kc * per + q, n = sl >> 1;
                        if (warp < 8 && (warp >> 2) == (sl & 1)) {
                            float4 x[16];
#pragma unroll
                            for (int c = 0; c < 16; c++) x[c] = (c < nsp) ? __ldcg(ps + (size_t)c * 4096 + n * 256) : make_float4(0.f, 0.f, 0.f, 0.f);
                            float4 acc = x[0];
#pragma unroll
                            for (int c = 1; c < 16; c++) { acc.x += x[c].x; acc.y += x[c].y; acc.z += x[c].z; acc.w += x[c].w; }
                            const int r = row0 + (warp & 3) * 16 + g, col = nt * 128 + (warp >> 2) * 64 + 8 * n + 2 * t;
                            *(uint32_t*)(prm.out + (size_t)r * 1280 + col) = pack_bf16(acc.x, acc.y);
                            *(uint32_t*)(prm.out + (size_t)(r + 8) * 1280 + col) = pack_bf16(acc.z, acc.w);
                        }
                    }
                } else if (warp < 8 && (shared_fin || lds32(s_last + 4) == (uint32_t)(nsp - 1))) {
                    const int wg = warp >> 2, r0 = wg * 64 + (warp & 3) * 16 + g;
                    const int n0 = shared_fin ? kc * (16 >> lsp) : 0, n1 = shared_fin ? n0 + (16 >> lsp) : 16;
                    const float4* ps = g_part + (size_t)(item - TICKET_G - 60 - kc) * 4096 + tid;
                    if (shared_fin) {
                        for (int n = n0; n < n1; n++) {
                            float4 x[16];
#pragma unroll
                            for (int c = 0; c < 16; c++) x[c] = (c < nsp) ? __ldcg(ps + (size_t)c * 4096 + n * 256) : make_float4(0.f, 0.f, 0.f, 0.f);
                            float4 acc = x[0];
#pragma unroll
                            for (int c = 1; c < 16; c++) { acc.x += x[c].x; acc.y += x[c].y; acc.z += x[c].z; acc.w += x[c].w; }
                            const int col = nt * 128 + 8 * n + 2 * t;
                            *(uint32_t*)(prm.out + (size_t)(rt * 128 + r0) * 1280 + col) = pack_bf16(acc.x, acc.y);
                            *(uint32_t*)(prm.out + (size_t)(rt * 128 + r0 + 8) * 1280 + col) = pack_bf16(acc.z, acc.w);
                        }
                    } else {
                        for (int nb = 0; nb < 16; nb += 4) {
                            float4 x[4][4];
#pragma unroll
                            for (int q = 0; q < 4; q++)
#pragma unroll
                                for (int c = 0; c < 4; c++) x[q][c] = (c < nsp) ? __ldcg(ps + (size_t)c * 4096 + (nb + q) * 256) : make_float4(0.f, 0.f, 0.f, 0.f);
#pragma unroll
                            for (int q = 0; q < 4; q++) {
                                const float4 acc = make_float4((x[q][0].x + x[q][1].x) + (x[q][2].x + x[q][3].x), (x[q][0].y + x[q][1].y) + (x[q][2].y + x[q][3].y),
                                                               (x[q][0].z + x[q][1].z) + (x[q][2].z + x[q][3].z), (x[q][0].w + x[q][1].w) + (x[q][2].w + x[q][3].w));
                                const int col = nt * 128 + 8 * (nb + q) + 2 * t;
                                *(uint32_t*)(prm.out + (size_t)(rt * 128 + r0) * 1280 + col) = pack_bf16(acc.x, acc.y);
                                *(uint32_t*)(prm.out + (size_t)(rt * 128 + r0 + 8) * 1280 + col) = pack_bf16(acc.z, acc.w);
                            }
                        }
                    }
                }
            }
        }
        fence_async_smem();
        if (tid == 256) sts32(s_item, draw());
        __syncthreads();
    }
    if (warp == 0) {
        unsigned old = 0;
        if (lane == 0) old = atomicAdd(&g_ctl.done, 1u);
        old = __shfl_sync(~0u, old, 0);
        if (old == gridDim.x - 1) {
            unsigned* w = (unsigned*)&g_ctl;
            for (int i = lane; i < (int)(sizeof(K2Ctl) / 4); i += 32) w[i] = 0;
        }
    }
}

typedef CUresult (*PFN_encodeTiled)(CUtensorMap*, CUtensorMapDataType, cuuint32_t, void*, const cuuint64_t*, const cuuint64_t*,
                                    const cuuint32_t*, const cuuint32_t*, CUtensorMapInterleave, CUtensorMapSwizzle,
                                    CUtensorMapL2promotion, CUtensorMapFloatOOBfill);
static PFN_encodeTiled get_encode() {
    static PFN_encodeTiled fn = nullptr;
    if (!fn) {
        void* p = nullptr; cudaDriverEntryPointQueryResult st;
        cudaGetDriverEntryPoint("cuTensorMapEncodeTiled", &p, cudaEnableDefault, &st);
        fn = (PFN_encodeTiled)p;
    }
    return fn;
}
static void make_map(CUtensorMap* m, const void* base, uint64_t cols, uint64_t rows, uint64_t row_stride_bytes, uint32_t box_c, uint32_t box_r,
                     CUtensorMapSwizzle swz = CU_TENSOR_MAP_SWIZZLE_128B, CUtensorMapL2promotion promo = CU_TENSOR_MAP_L2_PROMOTION_L2_128B) {
    cuuint64_t dims[2] = {cols, rows}; cuuint64_t strides[1] = {row_stride_bytes};
    cuuint32_t box[2] = {box_c, box_r}; cuuint32_t es[2] = {1, 1};
    get_encode()(m, CU_TENSOR_MAP_DATA_TYPE_BFLOAT16, 2, (void*)base, dims, strides, box, es, CU_TENSOR_MAP_INTERLEAVE_NONE, swz,
                 promo, CU_TENSOR_MAP_FLOAT_OOB_FILL_NONE);
}


extern "C" void kernel_launch(void* const* d_in, const int* in_sizes, int n_in, void* d_out, int out_size) {
    const __nv_bfloat16* x = (const __nv_bfloat16*)d_in[0];
    const __nv_bfloat16* mem0 = (const __nv_bfloat16*)d_in[1];
    const __nv_bfloat16* Wq = (const __nv_bfloat16*)d_in[2];
    const __nv_bfloat16* Wk = (const __nv_bfloat16*)d_in[3];
    const __nv_bfloat16* Wv = (const __nv_bfloat16*)d_in[4];
    const __nv_bfloat16* Wo = (const __nv_bfloat16*)d_in[5];
    CUtensorMap tmX, tmWq, tmWk, tmWv, tmWo128;
    make_map(&tmWo128, Wo, DM, 4096, DM * 2, 64, 128, CU_TENSOR_MAP_SWIZZLE_128B, WPROMO);
    make_map(&tmX, x, DM, S_, DM * 2, 64, 32);
    make_map(&tmWq, Wq, 4096, DM, 8192, 64, 128, CU_TENSOR_MAP_SWIZZLE_128B, WPROMO);
    make_map(&tmWk, Wk, 4096, DM, 8192, 64, 128, CU_TENSOR_MAP_SWIZZLE_128B, WPROMO);
    make_map(&tmWv, Wv, 4096, DM, 8192, 64, 128, CU_TENSOR_MAP_SWIZZLE_128B, WPROMO);
    cudaFuncSetAttribute(k1_chain, cudaFuncAttributeMaxDynamicSharedMemorySize, K1_SMEM);
    cudaStream_t st = cudaStreamPerThread;
    cudaLaunchConfig_t cfg = {};
    cfg.gridDim = dim3(K1_CTAS); cfg.blockDim = dim3(K1_THREADS); cfg.dynamicSmemBytes = K1_SMEM; cfg.stream = st;
    cudaLaunchAttribute at[1];
    at[0].id = cudaLaunchAttributeClusterDimension; at[0].val.clusterDim.x = 3; at[0].val.clusterDim.y = 1; at[0].val.clusterDim.z = 1;
    cfg.attrs = at; cfg.numAttrs = 1;
    K1Params prm{mem0, Wo, Wq, Wk, Wv};
    cudaLaunchKernelEx(&cfg, k1_chain, tmX, tmWq, tmWk, tmWv, tmWo128, prm);
    void* oxp; cudaGetSymbolAddress(&oxp, g_ox);
    CUtensorMap tmO, tmO64, tmWo, tmBq, tmBk, tmBv;
    make_map(&tmO64, oxp, 4096, S_, 8192, 64, 64);
    make_map(&tmO, oxp, 4096, S_, 8192, 64, 128);
    make_map(&tmWo, Wo, DM, 4096, DM * 2, 64, 64);
    make_map(&tmBq, d_in[7], DM, S_, DM * 2, 8, 256, CU_TENSOR_MAP_SWIZZLE_NONE);
    make_map(&tmBk, d_in[8], DM, S_, DM * 2, 8, 256, CU_TENSOR_MAP_SWIZZLE_NONE);
    make_map(&tmBv, d_in[9], DM, S_, DM * 2, 8, 256, CU_TENSOR_MAP_SWIZZLE_NONE);
    cudaFuncSetAttribute(k2_work, cudaFuncAttributeMaxDynamicSharedMemorySize, K2_SMEM);
    K2Params p2{(const __nv_bfloat16*)d_in[10], (const __nv_bfloat16*)d_in[11], (const __nv_bfloat16*)d_in[12], (__nv_bfloat16*)d_out};
    cudaLaunchConfig_t cfg2 = {};
    cfg2.gridDim = dim3(132); cfg2.blockDim = dim3(K2_THREADS); cfg2.dynamicSmemBytes = K2_SMEM; cfg2.stream = st;
    cudaLaunchAttribute at2[1];
    at2[0].id = cudaLaunchAttributeProgrammaticStreamSerialization; at2[0].val.programmaticStreamSerializationAllowed = PDL;
    cfg2.attrs = at2; cfg2.numAttrs = 1;
    cudaLaunchKernelEx(&cfg2, k2_work, tmO, tmO64, tmWo, tmBq, tmBk, tmBv, p2);
}
```
